```python
import torch

def _softmax(x, axis=-1):
    return torch.softmax(x, dim=axis)

def _gelu(x):
    return torch.nn.functional.gelu(x, approximate='tanh')

def _silu(x):
    return torch.nn.functional.silu(x)

def _sigmoid(x):
    return torch.sigmoid(x)

def _layernorm(x, axis=-1, eps=1e-05):
    m = x.mean(dim=axis, keepdim=True)
    v = x.var(dim=axis, keepdim=True, unbiased=False)
    return (x - m) / torch.sqrt(v + eps)

def _scatter_add(tgt, idx, src, axis=0):
    return tgt.clone().index_add_(axis, idx, src)

def _segment_sum(src, seg, n):
    out = torch.zeros((n,) + src.shape[1:], dtype=src.dtype)
    return out.index_add_(0, seg, src)

def _pad(x, pw):
    flat = tuple((v for pair in reversed(pw) for v in pair))
    return torch.nn.functional.pad(x, flat)
kernel_name = 'adaLN_cond__softmax_full_mha__dense_activation_silu__prompt'

def setup_inputs():

    _w = lambda a: (lambda t: t.to(torch.bfloat16) if t.is_floating_point() else t)(torch.as_tensor(a))

    def _A_setup():
        B, S, D = (1, 2048, 576)
        return {'x': _w((lambda *s: torch.randn(*s, dtype=torch.bfloat16) * 0.05)(B, S, D)), 'wqkv': _w((lambda *s: torch.randn(*s, dtype=torch.bfloat16) * 0.05)(D, 3 * D)), 'wo': _w((lambda *s: torch.randn(*s, dtype=torch.bfloat16) * 0.05)(D, D))}
    _A_in = _A_setup()

    def _B_setup():
        B, S, D, F = (1, 2048, 576, 4608)
        return {'x': _w((lambda *s: torch.randn(*s, dtype=torch.bfloat16) * 0.05)(B, S, D)), 'w1': _w((lambda *s: torch.randn(*s, dtype=torch.bfloat16) * 3.2)(D, F) * D ** (-0.5)), 'w2': _w((lambda *s: torch.randn(*s, dtype=torch.bfloat16) * 0.4)(F, D) * F ** (-0.5))}
    _B_in = _B_setup()
    return {'A_x': _A_in['x'], 'A_wqkv': _A_in['wqkv'], 'A_wo': _A_in['wo'], 'B_x': _B_in['x'], 'B_w1': _B_in['w1'], 'B_w2': _B_in['w2'], 'c': _w((lambda *s: torch.randn(*s, dtype=torch.bfloat16) * 0.1)(1, 576) * 8.0), 'w_mod': _w((lambda *s: torch.randn(*s, dtype=torch.bfloat16) * 0.1)(576, 6 * 576) * 576 ** (-0.5) * 8.0)}

def reference(A_x, A_wqkv, A_wo, B_x, B_w1, B_w2, c, w_mod):

    def _A_ref(x, wqkv, wo):
        B, S, D = x.shape
        H = 32
        Dh = D // H
        qkv = (lambda x, *d: x.permute(*d))((x @ wqkv).reshape(B, S, 3, H, Dh), 2, 0, 3, 1, 4)
        q, k, v = (qkv[0], qkv[1], qkv[2])
        scale = Dh ** (-0.5)
        scores = torch.einsum('bhqd,bhkd->bhqk', q, k) * scale
        p = _softmax(scores, axis=-1)
        o = torch.einsum('bhqk,bhkd->bhqd', p, v)
        return (lambda x, *d: x.permute(*d))(o, 0, 2, 1, 3).reshape(B, S, D) @ wo

    def _B_ref(x, w1, w2):
        h = torch.einsum('bsd,df->bsf', x, w1)
        h = _silu(h)
        out = torch.einsum('bsf,fd->bsd', h, w2)
        return out
    x = A_x
    mod = (_silu(c) @ w_mod).reshape(c.shape[0], 6, 1, -1)
    sa, ca, ga, sb, cb, gb = (mod[:, 0].clone(), mod[:, 1].clone(), mod[:, 2].clone(), mod[:, 3].clone(), mod[:, 4].clone(), mod[:, 5].clone())
    h = _layernorm(x, axis=-1) * (1 + ca) + sa
    x = x + ga * _A_ref(h, A_wqkv, A_wo)
    h = _layernorm(x, axis=-1) * (1 + cb) + sb
    x = x + gb * _B_ref(h, B_w1, B_w2)
    return x
```

```cpp
#include <cuda.h>
#include <cuda_bf16.h>
#include <cuda_runtime.h>
#include <stdint.h>

namespace {

constexpr int SEQ = 2048, DM = 576, NH = 32, DH = 18, FF = 4608, NQKV = 3 * DM;
constexpr int HEAD_BYTES = 256 * 384;

constexpr uint32_t ATT_POLY_BLOCKS = 0x7777;
__host__ __device__ constexpr bool att_poly_block(int blk) { return (ATT_POLY_BLOCKS >> (blk & 15)) & 1; }

__device__ uint4 g_coef[DM / 2];
__device__ __align__(1024) uint8_t g_qkv[(3 * NH + 4) * HEAD_BYTES];
__device__ __align__(1024) __nv_bfloat16 g_o[SEQ * DM];
__device__ __align__(1024) __nv_bfloat16 g_x1[SEQ * DM];
__device__ __align__(1024) __nv_bfloat16 g_h2[SEQ * DM];
__device__ __align__(1024) float g_red[16 * 9 * 2 * 4096];
__device__ unsigned int g_cnt[32];
__device__ unsigned long long g_stat[SEQ];
__device__ unsigned long long g_modx[2 * DM];

__device__ __forceinline__ uint32_t smem_u32(const void* p) { return (uint32_t)__cvta_generic_to_shared(p); }
__device__ __forceinline__ void mbar_init(uint32_t bar, uint32_t cnt) {
  asm volatile("mbarrier.init.shared::cta.b64 [%0], %1;" ::"r"(bar), "r"(cnt) : "memory");
}
__device__ __forceinline__ void mbar_expect_tx(uint32_t bar, uint32_t bytes) {
  asm volatile("mbarrier.arrive.expect_tx.shared::cta.b64 _, [%0], %1;" ::"r"(bar), "r"(bytes) : "memory");
}
__device__ __forceinline__ void mbar_arrive(uint32_t bar) {
  asm volatile("mbarrier.arrive.shared::cta.b64 _, [%0];" ::"r"(bar) : "memory");
}
__device__ __forceinline__ void mbar_arrive_cluster(uint32_t bar_cluster_addr) {
  asm volatile("mbarrier.arrive.shared::cluster.b64 _, [%0];" ::"r"(bar_cluster_addr) : "memory");
}
__device__ __forceinline__ bool mbar_test(uint32_t bar, uint32_t parity) {
  uint32_t ok;
  asm volatile("{\n.reg .pred p;\nmbarrier.test_wait.parity.shared::cta.b64 p, [%1], %2;\nselp.u32 %0, 1, 0, p;\n}"
               : "=r"(ok) : "r"(bar), "r"(parity) : "memory");
  return ok != 0;
}
__device__ __forceinline__ void mbar_wait(uint32_t bar, uint32_t parity) {
  asm volatile(
      "{\n.reg .pred p;\n.reg .u32 n;\nmov.u32 n, 0;\n"
      "WAIT_%=:\n"
      "mbarrier.try_wait.parity.shared::cta.b64 p, [%0], %1;\n"
      "@p bra DONE_%=;\n"
      "add.u32 n, n, 1;\nsetp.lt.u32 p, n, 0x400000;\n@p bra WAIT_%=;\n"
      "DONE_%=:\n}"
      ::"r"(bar), "r"(parity) : "memory");
}
__device__ __forceinline__ bool elect_one() {
  uint32_t r;
  asm volatile("{\n.reg .pred p;\nelect.sync _|p, 0xffffffff;\nselp.u32 %0, 1, 0, p;\n}" : "=r"(r));
  return r != 0;
}
__device__ __forceinline__ void fence_mbar_init() { asm volatile("fence.mbarrier_init.release.cluster;" ::: "memory"); }
__device__ __forceinline__ void fence_proxy_async() { asm volatile("fence.proxy.async.shared::cta;" ::: "memory"); }
__device__ __forceinline__ void bulk_g2s(uint32_t dst, const void* src, uint32_t bytes, uint32_t bar) {
  asm volatile("cp.async.bulk.shared::cluster.global.mbarrier::complete_tx::bytes [%0], [%1], %2, [%3];"
               ::"r"(dst), "l"(src), "r"(bytes), "r"(bar) : "memory");
}
__device__ __forceinline__ void bulk_prefetch_l2(const void* src, uint32_t bytes) {
  asm volatile("cp.async.bulk.prefetch.L2.global [%0], %1;" ::"l"(src), "r"(bytes) : "memory");
}
__device__ __forceinline__ void tma_2d(uint32_t dst, const CUtensorMap* m, int c0, int c1, uint32_t bar) {
  asm volatile("cp.async.bulk.tensor.2d.shared::cluster.global.mbarrier::complete_tx::bytes [%0], [%1, {%3, %4}], [%2];"
               ::"r"(dst), "l"(m), "r"(bar), "r"(c0), "r"(c1) : "memory");
}
__device__ __forceinline__ void tma_2d_mc(uint32_t dst, const CUtensorMap* m, int c0, int c1, uint32_t bar, uint16_t mask) {
  asm volatile("cp.async.bulk.tensor.2d.shared::cluster.global.mbarrier::complete_tx::bytes.multicast::cluster [%0], [%1, {%3, %4}], [%2], %5;"
               ::"r"(dst), "l"(m), "r"(bar), "r"(c0), "r"(c1), "h"(mask) : "memory");
}
__device__ __forceinline__ void tma_3d_mc(uint32_t dst, const CUtensorMap* m, int c0, int c1, int c2, uint32_t bar, uint16_t mask) {
  asm volatile("cp.async.bulk.tensor.3d.shared::cluster.global.mbarrier::complete_tx::bytes.multicast::cluster [%0], [%1, {%3, %4, %5}], [%2], %6;"
               ::"r"(dst), "l"(m), "r"(bar), "r"(c0), "r"(c1), "r"(c2), "h"(mask) : "memory");
}
__device__ __forceinline__ void prefetch_tmap(const CUtensorMap* m) {
  asm volatile("prefetch.tensormap [%0];" ::"l"(m) : "memory");
}
__device__ __forceinline__ void wg_fence() { asm volatile("wgmma.fence.sync.aligned;" ::: "memory"); }
__device__ __forceinline__ void wg_commit() { asm volatile("wgmma.commit_group.sync.aligned;" ::: "memory"); }
template <int N> __device__ __forceinline__ void wg_wait() { asm volatile("wgmma.wait_group.sync.aligned %0;" ::"n"(N) : "memory"); }
__device__ __forceinline__ void pdl_launch() { asm volatile("griddepcontrol.launch_dependents;" ::: "memory"); }
__device__ __forceinline__ void pdl_wait() { asm volatile("griddepcontrol.wait;" ::: "memory"); }
__device__ __forceinline__ void named_bar_sync(int id, int n) { asm volatile("bar.sync %0, %1;" ::"r"(id), "r"(n) : "memory"); }
__device__ __forceinline__ void named_bar_arrive(int id, int n) { asm volatile("bar.arrive %0, %1;" ::"r"(id), "r"(n) : "memory"); }
__device__ __forceinline__ void cluster_arrive() { asm volatile("barrier.cluster.arrive.relaxed.aligned;" ::: "memory"); }
__device__ __forceinline__ void cluster_wait() { asm volatile("barrier.cluster.wait.aligned;" ::: "memory"); }
__device__ __forceinline__ uint32_t mapa(uint32_t addr, uint32_t rank) {
  uint32_t r; asm("mapa.shared::cluster.u32 %0, %1, %2;" : "=r"(r) : "r"(addr), "r"(rank)); return r;
}
__device__ __forceinline__ uint32_t cluster_rank() { uint32_t r; asm("mov.u32 %0, %%cluster_ctarank;" : "=r"(r)); return r; }
template <int R> __device__ __forceinline__ void reg_alloc() { asm volatile("setmaxnreg.inc.sync.aligned.u32 %0;" ::"n"(R)); }
template <int R> __device__ __forceinline__ void reg_dealloc() { asm volatile("setmaxnreg.dec.sync.aligned.u32 %0;" ::"n"(R)); }

__device__ __forceinline__ uint32_t pack_bf16(float lo, float hi) {
  uint32_t r; asm("cvt.rn.bf16x2.f32 %0, %1, %2;" : "=r"(r) : "f"(hi), "f"(lo)); return r;
}
__device__ __forceinline__ float ex2(float x) { float r; asm("ex2.approx.ftz.f32 %0, %1;" : "=f"(r) : "f"(x)); return r; }
__device__ __forceinline__ float bf_lo(uint32_t v) { return __uint_as_float(v << 16); }
__device__ __forceinline__ float bf_hi(uint32_t v) { return __uint_as_float(v & 0xffff0000u); }
__device__ __forceinline__ uint32_t desc_addr(uint32_t a) { return (a & 0x3FFFFu) >> 4; }
__device__ __forceinline__ uint64_t mk64(uint32_t lo, uint32_t hi) {
  uint64_t r; asm("mov.b64 %0, {%1, %2};" : "=l"(r) : "r"(lo), "r"(hi)); return r;
}
__device__ __forceinline__ uint32_t hfma2_bf16(uint32_t a, uint32_t b, uint32_t c) {
  uint32_t r; asm("fma.rn.bf16x2 %0, %1, %2, %3;" : "=r"(r) : "r"(a), "r"(b), "r"(c)); return r;
}
__device__ __forceinline__ uint32_t ld_acquire_gpu(const unsigned int* p) {
  uint32_t v; asm volatile("ld.acquire.gpu.global.u32 %0, [%1];" : "=r"(v) : "l"(p) : "memory"); return v;
}
__device__ __forceinline__ void publish_add(unsigned int* p, uint32_t v) {
  asm volatile("fence.proxy.async.global;" ::: "memory");
  asm volatile("red.release.gpu.global.add.u32 [%0], %1;" ::"l"(p), "r"(v) : "memory");
}
__device__ __forceinline__ void st_tagged(unsigned long long* p, uint32_t v, uint32_t tag) {
  asm volatile("st.relaxed.gpu.global.u64 [%0], %1;" ::"l"(p), "l"(((unsigned long long)tag << 32) | v) : "memory");
}
__device__ __forceinline__ unsigned long long ld_tagged(const unsigned long long* p) {
  unsigned long long v; asm volatile("ld.relaxed.gpu.global.u64 %0, [%1];" : "=l"(v) : "l"(p) : "memory"); return v;
}
__device__ __forceinline__ void spin_until_ge(const unsigned int* p, uint32_t target) {
  for (uint32_t n = 0; n < (1u << 22); n++) {
    if (ld_acquire_gpu(p) >= target) break;
  }
}
__device__ __forceinline__ void sts128(uint32_t addr, uint32_t a, uint32_t b, uint32_t c, uint32_t d) {
  asm volatile("st.shared.v4.u32 [%0], {%1, %2, %3, %4};" ::"r"(addr), "r"(a), "r"(b), "r"(c), "r"(d) : "memory");
}
__device__ __forceinline__ uint4 lds128(uint32_t addr) {
  uint4 v; asm volatile("ld.shared.v4.u32 {%0, %1, %2, %3}, [%4];" : "=r"(v.x), "=r"(v.y), "=r"(v.z), "=r"(v.w) : "r"(addr)); return v;
}
__device__ __forceinline__ uint32_t lds32(uint32_t addr) {
  uint32_t v; asm volatile("ld.shared.u32 %0, [%1];" : "=r"(v) : "r"(addr)); return v;
}
__device__ __forceinline__ void ldmatrix_x4(uint32_t addr, uint32_t& a0, uint32_t& a1, uint32_t& a2, uint32_t& a3) {
  asm volatile("ldmatrix.sync.aligned.m8n8.x4.shared.b16 {%0, %1, %2, %3}, [%4];"
               : "=r"(a0), "=r"(a1), "=r"(a2), "=r"(a3) : "r"(addr));
}
__device__ __forceinline__ void stmatrix_x4(uint32_t addr, uint32_t a0, uint32_t a1, uint32_t a2, uint32_t a3) {
  asm volatile("stmatrix.sync.aligned.m8n8.x4.shared.b16 [%0], {%1, %2, %3, %4};" ::"r"(addr), "r"(a0), "r"(a1), "r"(a2), "r"(a3) : "memory");
}
__device__ __forceinline__ void tma_store_2d(const CUtensorMap* m, uint32_t src, int c0, int c1) {
  asm volatile("cp.async.bulk.tensor.2d.global.shared::cta.bulk_group [%0, {%2, %3}], [%1];" ::"l"(m), "r"(src), "r"(c0), "r"(c1) : "memory");
}
__device__ __forceinline__ void bulk_commit() { asm volatile("cp.async.bulk.commit_group;" ::: "memory"); }
__device__ __forceinline__ void bulk_wait_read() { asm volatile("cp.async.bulk.wait_group.read 0;" ::: "memory"); }
__device__ __forceinline__ void store_frag_tile(uint32_t tile, int row0, int lane, const uint32_t (&v)[16]) {
  const int row = row0 + (lane & 15);
  const uint32_t base = tile + row * 128;
#pragma unroll
  for (int jj = 0; jj < 8; jj += 2)
    stmatrix_x4(base + (((jj + (lane >> 4)) ^ (row & 7)) << 4), v[2 * jj], v[2 * jj + 1], v[2 * jj + 2], v[2 * jj + 3]);
}
__device__ __forceinline__ void load_frag_tile(uint32_t tile, int row0, int lane, uint32_t (&v)[16]) {
  const int row = row0 + (lane & 15);
  const uint32_t base = tile + row * 128;
#pragma unroll
  for (int jj = 0; jj < 8; jj += 2)
    ldmatrix_x4(base + (((jj + (lane >> 4)) ^ (row & 7)) << 4), v[2 * jj], v[2 * jj + 1], v[2 * jj + 2], v[2 * jj + 3]);
}
__device__ __forceinline__ float tanh_approx(float x) { float r; asm("tanh.approx.f32 %0, %1;" : "=f"(r) : "f"(x)); return r; }

__device__ __forceinline__ void wgmma_rs_n128(float (&d)[64], uint32_t a0, uint32_t a1, uint32_t a2, uint32_t a3, uint64_t db, int scale_d) {
  asm volatile("{\n.reg .pred p;\nsetp.ne.b32 p, %69, 0;\n"
      "wgmma.mma_async.sync.aligned.m64n128k16.f32.bf16.bf16 {"
      "%0, %1, %2, %3, %4, %5, %6, %7, %8, %9, %10, %11, %12, %13, %14, %15, %16, %17, %18, %19, %20, %21, %22, %23, "
      "%24, %25, %26, %27, %28, %29, %30, %31, %32, %33, %34, %35, %36, %37, %38, %39, %40, %41, %42, %43, %44, %45, "
      "%46, %47, %48, %49, %50, %51, %52, %53, %54, %55, %56, %57, %58, %59, %60, %61, %62, %63"
      "}, {%64, %65, %66, %67}, %68, p, 1, 1, 0;\n}\n"
      : "+f"(d[0]), "+f"(d[1]), "+f"(d[2]), "+f"(d[3]), "+f"(d[4]), "+f"(d[5]), "+f"(d[6]), "+f"(d[7]), "+f"(d[8]),
        "+f"(d[9]), "+f"(d[10]), "+f"(d[11]), "+f"(d[12]), "+f"(d[13]), "+f"(d[14]), "+f"(d[15]), "+f"(d[16]),
        "+f"(d[17]), "+f"(d[18]), "+f"(d[19]), "+f"(d[20]), "+f"(d[21]), "+f"(d[22]), "+f"(d[23]), "+f"(d[24]),
        "+f"(d[25]), "+f"(d[26]), "+f"(d[27]), "+f"(d[28]), "+f"(d[29]), "+f"(d[30]), "+f"(d[31]), "+f"(d[32]),
        "+f"(d[33]), "+f"(d[34]), "+f"(d[35]), "+f"(d[36]), "+f"(d[37]), "+f"(d[38]), "+f"(d[39]), "+f"(d[40]),
        "+f"(d[41]), "+f"(d[42]), "+f"(d[43]), "+f"(d[44]), "+f"(d[45]), "+f"(d[46]), "+f"(d[47]), "+f"(d[48]),
        "+f"(d[49]), "+f"(d[50]), "+f"(d[51]), "+f"(d[52]), "+f"(d[53]), "+f"(d[54]), "+f"(d[55]), "+f"(d[56]),
        "+f"(d[57]), "+f"(d[58]), "+f"(d[59]), "+f"(d[60]), "+f"(d[61]), "+f"(d[62]), "+f"(d[63])
      : "r"(a0), "r"(a1), "r"(a2), "r"(a3), "l"(db), "r"(scale_d));
}
__device__ __forceinline__ void wgmma_rs_n128_init(float (&d)[64], uint32_t a0, uint32_t a1, uint32_t a2, uint32_t a3, uint64_t db) {
  asm volatile("wgmma.mma_async.sync.aligned.m64n128k16.f32.bf16.bf16 {"
      "%0, %1, %2, %3, %4, %5, %6, %7, %8, %9, %10, %11, %12, %13, %14, %15, %16, %17, %18, %19, %20, %21, %22, %23, "
      "%24, %25, %26, %27, %28, %29, %30, %31, %32, %33, %34, %35, %36, %37, %38, %39, %40, %41, %42, %43, %44, %45, "
      "%46, %47, %48, %49, %50, %51, %52, %53, %54, %55, %56, %57, %58, %59, %60, %61, %62, %63"
      "}, {%64, %65, %66, %67}, %68, 0, 1, 1, 0;\n"
      : "=f"(d[0]), "=f"(d[1]), "=f"(d[2]), "=f"(d[3]), "=f"(d[4]), "=f"(d[5]), "=f"(d[6]), "=f"(d[7]), "=f"(d[8]),
        "=f"(d[9]), "=f"(d[10]), "=f"(d[11]), "=f"(d[12]), "=f"(d[13]), "=f"(d[14]), "=f"(d[15]), "=f"(d[16]),
        "=f"(d[17]), "=f"(d[18]), "=f"(d[19]), "=f"(d[20]), "=f"(d[21]), "=f"(d[22]), "=f"(d[23]), "=f"(d[24]),
        "=f"(d[25]), "=f"(d[26]), "=f"(d[27]), "=f"(d[28]), "=f"(d[29]), "=f"(d[30]), "=f"(d[31]), "=f"(d[32]),
        "=f"(d[33]), "=f"(d[34]), "=f"(d[35]), "=f"(d[36]), "=f"(d[37]), "=f"(d[38]), "=f"(d[39]), "=f"(d[40]),
        "=f"(d[41]), "=f"(d[42]), "=f"(d[43]), "=f"(d[44]), "=f"(d[45]), "=f"(d[46]), "=f"(d[47]), "=f"(d[48]),
        "=f"(d[49]), "=f"(d[50]), "=f"(d[51]), "=f"(d[52]), "=f"(d[53]), "=f"(d[54]), "=f"(d[55]), "=f"(d[56]),
        "=f"(d[57]), "=f"(d[58]), "=f"(d[59]), "=f"(d[60]), "=f"(d[61]), "=f"(d[62]), "=f"(d[63])
      : "r"(a0), "r"(a1), "r"(a2), "r"(a3), "l"(db));
}
__device__ __forceinline__ void wgmma_rs_n24_tb(float (&d)[12], uint32_t a0, uint32_t a1, uint32_t a2, uint32_t a3, uint64_t db, int scale_d) {
  asm volatile("{\n.reg .pred p;\nsetp.ne.b32 p, %17, 0;\n"
      "wgmma.mma_async.sync.aligned.m64n24k16.f32.bf16.bf16 {"
      "%0, %1, %2, %3, %4, %5, %6, %7, %8, %9, %10, %11"
      "}, {%12, %13, %14, %15}, %16, p, 1, 1, 1;\n}\n"
      : "+f"(d[0]), "+f"(d[1]), "+f"(d[2]), "+f"(d[3]), "+f"(d[4]), "+f"(d[5]), "+f"(d[6]), "+f"(d[7]), "+f"(d[8]),
        "+f"(d[9]), "+f"(d[10]), "+f"(d[11])
      : "r"(a0), "r"(a1), "r"(a2), "r"(a3), "l"(db), "r"(scale_d));
}
__device__ __forceinline__ void wgmma_ss_n64_tb(float (&d)[32], uint64_t da, uint64_t db, int scale_d) {
  asm volatile("{\n.reg .pred p;\nsetp.ne.b32 p, %34, 0;\n"
      "wgmma.mma_async.sync.aligned.m64n64k16.f32.bf16.bf16 {"
      "%0, %1, %2, %3, %4, %5, %6, %7, %8, %9, %10, %11, %12, %13, %14, %15, %16, %17, %18, %19, %20, %21, %22, %23, "
      "%24, %25, %26, %27, %28, %29, %30, %31"
      "}, %32, %33, p, 1, 1, 0, 1;\n}\n"
      : "+f"(d[0]), "+f"(d[1]), "+f"(d[2]), "+f"(d[3]), "+f"(d[4]), "+f"(d[5]), "+f"(d[6]), "+f"(d[7]), "+f"(d[8]),
        "+f"(d[9]), "+f"(d[10]), "+f"(d[11]), "+f"(d[12]), "+f"(d[13]), "+f"(d[14]), "+f"(d[15]), "+f"(d[16]),
        "+f"(d[17]), "+f"(d[18]), "+f"(d[19]), "+f"(d[20]), "+f"(d[21]), "+f"(d[22]), "+f"(d[23]), "+f"(d[24]),
        "+f"(d[25]), "+f"(d[26]), "+f"(d[27]), "+f"(d[28]), "+f"(d[29]), "+f"(d[30]), "+f"(d[31])
      : "l"(da), "l"(db), "r"(scale_d));
}
__device__ __forceinline__ void wgmma_rs_n64_tb(float (&d)[32], uint32_t a0, uint32_t a1, uint32_t a2, uint32_t a3, uint64_t db, int scale_d) {
  asm volatile("{\n.reg .pred p;\nsetp.ne.b32 p, %37, 0;\n"
      "wgmma.mma_async.sync.aligned.m64n64k16.f32.bf16.bf16 {"
      "%0, %1, %2, %3, %4, %5, %6, %7, %8, %9, %10, %11, %12, %13, %14, %15, %16, %17, %18, %19, %20, %21, %22, %23, "
      "%24, %25, %26, %27, %28, %29, %30, %31"
      "}, {%32, %33, %34, %35}, %36, p, 1, 1, 1;\n}\n"
      : "+f"(d[0]), "+f"(d[1]), "+f"(d[2]), "+f"(d[3]), "+f"(d[4]), "+f"(d[5]), "+f"(d[6]), "+f"(d[7]), "+f"(d[8]),
        "+f"(d[9]), "+f"(d[10]), "+f"(d[11]), "+f"(d[12]), "+f"(d[13]), "+f"(d[14]), "+f"(d[15]), "+f"(d[16]),
        "+f"(d[17]), "+f"(d[18]), "+f"(d[19]), "+f"(d[20]), "+f"(d[21]), "+f"(d[22]), "+f"(d[23]), "+f"(d[24]),
        "+f"(d[25]), "+f"(d[26]), "+f"(d[27]), "+f"(d[28]), "+f"(d[29]), "+f"(d[30]), "+f"(d[31])
      : "r"(a0), "r"(a1), "r"(a2), "r"(a3), "l"(db), "r"(scale_d));
}
__device__ __forceinline__ void wgmma_ss_n64_tb_init(float (&d)[32], uint64_t da, uint64_t db) {
  asm volatile("wgmma.mma_async.sync.aligned.m64n64k16.f32.bf16.bf16 {"
      "%0, %1, %2, %3, %4, %5, %6, %7, %8, %9, %10, %11, %12, %13, %14, %15, %16, %17, %18, %19, %20, %21, %22, %23, "
      "%24, %25, %26, %27, %28, %29, %30, %31"
      "}, %32, %33, 0, 1, 1, 0, 1;\n"
      : "=f"(d[0]), "=f"(d[1]), "=f"(d[2]), "=f"(d[3]), "=f"(d[4]), "=f"(d[5]), "=f"(d[6]), "=f"(d[7]), "=f"(d[8]),
        "=f"(d[9]), "=f"(d[10]), "=f"(d[11]), "=f"(d[12]), "=f"(d[13]), "=f"(d[14]), "=f"(d[15]), "=f"(d[16]),
        "=f"(d[17]), "=f"(d[18]), "=f"(d[19]), "=f"(d[20]), "=f"(d[21]), "=f"(d[22]), "=f"(d[23]), "=f"(d[24]),
        "=f"(d[25]), "=f"(d[26]), "=f"(d[27]), "=f"(d[28]), "=f"(d[29]), "=f"(d[30]), "=f"(d[31])
      : "l"(da), "l"(db));
}
__device__ __forceinline__ void wgmma_rs_n64_tb_init(float (&d)[32], uint32_t a0, uint32_t a1, uint32_t a2, uint32_t a3, uint64_t db) {
  asm volatile("wgmma.mma_async.sync.aligned.m64n64k16.f32.bf16.bf16 {"
      "%0, %1, %2, %3, %4, %5, %6, %7, %8, %9, %10, %11, %12, %13, %14, %15, %16, %17, %18, %19, %20, %21, %22, %23, "
      "%24, %25, %26, %27, %28, %29, %30, %31"
      "}, {%32, %33, %34, %35}, %36, 0, 1, 1, 1;\n"
      : "=f"(d[0]), "=f"(d[1]), "=f"(d[2]), "=f"(d[3]), "=f"(d[4]), "=f"(d[5]), "=f"(d[6]), "=f"(d[7]), "=f"(d[8]),
        "=f"(d[9]), "=f"(d[10]), "=f"(d[11]), "=f"(d[12]), "=f"(d[13]), "=f"(d[14]), "=f"(d[15]), "=f"(d[16]),
        "=f"(d[17]), "=f"(d[18]), "=f"(d[19]), "=f"(d[20]), "=f"(d[21]), "=f"(d[22]), "=f"(d[23]), "=f"(d[24]),
        "=f"(d[25]), "=f"(d[26]), "=f"(d[27]), "=f"(d[28]), "=f"(d[29]), "=f"(d[30]), "=f"(d[31])
      : "r"(a0), "r"(a1), "r"(a2), "r"(a3), "l"(db));
}
__device__ __forceinline__ void wgmma_ss_n128_tb(float (&d)[64], uint64_t da, uint64_t db, int scale_d) {
  asm volatile("{\n.reg .pred p;\nsetp.ne.b32 p, %66, 0;\n"
      "wgmma.mma_async.sync.aligned.m64n128k16.f32.bf16.bf16 {"
      "%0, %1, %2, %3, %4, %5, %6, %7, %8, %9, %10, %11, %12, %13, %14, %15, %16, %17, %18, %19, %20, %21, %22, %23, "
      "%24, %25, %26, %27, %28, %29, %30, %31, %32, %33, %34, %35, %36, %37, %38, %39, %40, %41, %42, %43, %44, %45, "
      "%46, %47, %48, %49, %50, %51, %52, %53, %54, %55, %56, %57, %58, %59, %60, %61, %62, %63"
      "}, %64, %65, p, 1, 1, 0, 1;\n}\n"
      : "+f"(d[0]), "+f"(d[1]), "+f"(d[2]), "+f"(d[3]), "+f"(d[4]), "+f"(d[5]), "+f"(d[6]), "+f"(d[7]), "+f"(d[8]),
        "+f"(d[9]), "+f"(d[10]), "+f"(d[11]), "+f"(d[12]), "+f"(d[13]), "+f"(d[14]), "+f"(d[15]), "+f"(d[16]),
        "+f"(d[17]), "+f"(d[18]), "+f"(d[19]), "+f"(d[20]), "+f"(d[21]), "+f"(d[22]), "+f"(d[23]), "+f"(d[24]),
        "+f"(d[25]), "+f"(d[26]), "+f"(d[27]), "+f"(d[28]), "+f"(d[29]), "+f"(d[30]), "+f"(d[31]), "+f"(d[32]),
        "+f"(d[33]), "+f"(d[34]), "+f"(d[35]), "+f"(d[36]), "+f"(d[37]), "+f"(d[38]), "+f"(d[39]), "+f"(d[40]),
        "+f"(d[41]), "+f"(d[42]), "+f"(d[43]), "+f"(d[44]), "+f"(d[45]), "+f"(d[46]), "+f"(d[47]), "+f"(d[48]),
        "+f"(d[49]), "+f"(d[50]), "+f"(d[51]), "+f"(d[52]), "+f"(d[53]), "+f"(d[54]), "+f"(d[55]), "+f"(d[56]),
        "+f"(d[57]), "+f"(d[58]), "+f"(d[59]), "+f"(d[60]), "+f"(d[61]), "+f"(d[62]), "+f"(d[63])
      : "l"(da), "l"(db), "r"(scale_d));
}
__device__ __forceinline__ void wgmma_ss_n32_tb(float (&d)[16], uint64_t da, uint64_t db, int scale_d) {
  asm volatile("{\n.reg .pred p;\nsetp.ne.b32 p, %18, 0;\n"
      "wgmma.mma_async.sync.aligned.m64n32k16.f32.bf16.bf16 {"
      "%0, %1, %2, %3, %4, %5, %6, %7, %8, %9, %10, %11, %12, %13, %14, %15"
      "}, %16, %17, p, 1, 1, 0, 1;\n}\n"
      : "+f"(d[0]), "+f"(d[1]), "+f"(d[2]), "+f"(d[3]), "+f"(d[4]), "+f"(d[5]), "+f"(d[6]), "+f"(d[7]), "+f"(d[8]),
        "+f"(d[9]), "+f"(d[10]), "+f"(d[11]), "+f"(d[12]), "+f"(d[13]), "+f"(d[14]), "+f"(d[15])
      : "l"(da), "l"(db), "r"(scale_d));
}
__device__ __forceinline__ void wgmma_rs_n224_tb(float (&d)[112], uint32_t a0, uint32_t a1, uint32_t a2, uint32_t a3, uint64_t db, int scale_d) {
  asm volatile("{\n.reg .pred p;\nsetp.ne.b32 p, %117, 0;\n"
      "wgmma.mma_async.sync.aligned.m64n224k16.f32.bf16.bf16 {"
      "%0, %1, %2, %3, %4, %5, %6, %7, %8, %9, %10, %11, %12, %13, %14, %15, %16, %17, %18, %19, %20, %21, %22, %23, "
      "%24, %25, %26, %27, %28, %29, %30, %31, %32, %33, %34, %35, %36, %37, %38, %39, %40, %41, %42, %43, %44, %45, "
      "%46, %47, %48, %49, %50, %51, %52, %53, %54, %55, %56, %57, %58, %59, %60, %61, %62, %63, %64, %65, %66, %67, "
      "%68, %69, %70, %71, %72, %73, %74, %75, %76, %77, %78, %79, %80, %81, %82, %83, %84, %85, %86, %87, %88, %89, "
      "%90, %91, %92, %93, %94, %95, %96, %97, %98, %99, %100, %101, %102, %103, %104, %105, %106, %107, %108, %109, "
      "%110, %111"
      "}, {%112, %113, %114, %115}, %116, p, 1, 1, 1;\n}\n"
      : "+f"(d[0]), "+f"(d[1]), "+f"(d[2]), "+f"(d[3]), "+f"(d[4]), "+f"(d[5]), "+f"(d[6]), "+f"(d[7]), "+f"(d[8]),
        "+f"(d[9]), "+f"(d[10]), "+f"(d[11]), "+f"(d[12]), "+f"(d[13]), "+f"(d[14]), "+f"(d[15]), "+f"(d[16]),
        "+f"(d[17]), "+f"(d[18]), "+f"(d[19]), "+f"(d[20]), "+f"(d[21]), "+f"(d[22]), "+f"(d[23]), "+f"(d[24]),
        "+f"(d[25]), "+f"(d[26]), "+f"(d[27]), "+f"(d[28]), "+f"(d[29]), "+f"(d[30]), "+f"(d[31]), "+f"(d[32]),
        "+f"(d[33]), "+f"(d[34]), "+f"(d[35]), "+f"(d[36]), "+f"(d[37]), "+f"(d[38]), "+f"(d[39]), "+f"(d[40]),
        "+f"(d[41]), "+f"(d[42]), "+f"(d[43]), "+f"(d[44]), "+f"(d[45]), "+f"(d[46]), "+f"(d[47]), "+f"(d[48]),
        "+f"(d[49]), "+f"(d[50]), "+f"(d[51]), "+f"(d[52]), "+f"(d[53]), "+f"(d[54]), "+f"(d[55]), "+f"(d[56]),
        "+f"(d[57]), "+f"(d[58]), "+f"(d[59]), "+f"(d[60]), "+f"(d[61]), "+f"(d[62]), "+f"(d[63]), "+f"(d[64]),
        "+f"(d[65]), "+f"(d[66]), "+f"(d[67]), "+f"(d[68]), "+f"(d[69]), "+f"(d[70]), "+f"(d[71]), "+f"(d[72]),
        "+f"(d[73]), "+f"(d[74]), "+f"(d[75]), "+f"(d[76]), "+f"(d[77]), "+f"(d[78]), "+f"(d[79]), "+f"(d[80]),
        "+f"(d[81]), "+f"(d[82]), "+f"(d[83]), "+f"(d[84]), "+f"(d[85]), "+f"(d[86]), "+f"(d[87]), "+f"(d[88]),
        "+f"(d[89]), "+f"(d[90]), "+f"(d[91]), "+f"(d[92]), "+f"(d[93]), "+f"(d[94]), "+f"(d[95]), "+f"(d[96]),
        "+f"(d[97]), "+f"(d[98]), "+f"(d[99]), "+f"(d[100]), "+f"(d[101]), "+f"(d[102]), "+f"(d[103]), "+f"(d[104]),
        "+f"(d[105]), "+f"(d[106]), "+f"(d[107]), "+f"(d[108]), "+f"(d[109]), "+f"(d[110]), "+f"(d[111])
      : "r"(a0), "r"(a1), "r"(a2), "r"(a3), "l"(db), "r"(scale_d));
}

constexpr int QKV_STAGES = 5, QKV_STAGE = 14336;
constexpr int QKV_A = 0, QKV_W = 147456, QKV_TAB = QKV_W + QKV_STAGES * QKV_STAGE, QKV_ROW = QKV_TAB + 2304,
              QKV_OFF = QKV_ROW + 1024, QKV_BAR = QKV_OFF + 512, QKV_SMEM = QKV_BAR + 256 + 1024;
constexpr int QKV_SLAB = QKV_A + 6 * 16384, QKV_SC = QKV_SLAB + 576 * 64;

__global__ void __launch_bounds__(384, 1)
qkv_kernel(const __grid_constant__ CUtensorMap tmX, const __grid_constant__ CUtensorMap tmW, const __grid_constant__ CUtensorMap tmM,
           const __nv_bfloat16* __restrict__ x, const __nv_bfloat16* __restrict__ cvec, const __nv_bfloat16* __restrict__ wqkv) {
  extern __shared__ uint8_t smem_raw[];
  const uint32_t sb = (smem_u32(smem_raw) + 1023) & ~1023u;
  const uint32_t sA = sb + QKV_A, sW = sb + QKV_W, sTab = sb + QKV_TAB, sRow = sb + QKV_ROW, sOff = sb + QKV_OFF;
  const uint32_t sSlab = sb + QKV_SLAB, sSc = sb + QKV_SC;
  const uint32_t bFull = sb + QKV_BAR, bEmpty = bFull + 8 * QKV_STAGES, bA = bEmpty + 8 * QKV_STAGES, bSlab = bA + 8 * 3;
  const int tid = threadIdx.x, lane = tid & 31, wid = __shfl_sync(0xffffffffu, tid >> 5, 0);
  const int rb = blockIdx.x & 15, ct = blockIdx.x >> 4;
  const uint32_t rank = cluster_rank();
  const int n0 = ct * 224;

  auto load_slab = [&]() {
    mbar_expect_tx(bSlab, 576 * 64);
#pragma unroll
    for (int i = 0; i < 3; i++) tma_2d(sSlab + i * 192 * 64, &tmM, blockIdx.x * 32, i * 192, bSlab);
  };
  auto load_x = [&](int g0, int g1) {
#pragma unroll 1
    for (int i = g0; i < g1; i++) {
      mbar_expect_tx(bA + 8 * i, 3 * 16384);
#pragma unroll 1
      for (int j = 3 * i; j < 3 * i + 3; j++) tma_2d(sA + j * 16384, &tmX, j * 64, rb * 128, bA + 8 * i);
    }
  };
  const bool gemv = blockIdx.x < 108;
  if (tid == 0) { prefetch_tmap(&tmM); prefetch_tmap(&tmX); prefetch_tmap(&tmW); }
  if (wid == 8 && elect_one()) {
#pragma unroll
    for (int i = 0; i < QKV_STAGES; i++) { mbar_init(bFull + 8 * i, 1); mbar_init(bEmpty + 8 * i, 4); }
#pragma unroll
    for (int i = 0; i < 4; i++) mbar_init(bA + 8 * i, 1);
    fence_mbar_init();
    if (blockIdx.x < 36) load_slab(); else load_x(0, gemv ? 2 : 3);
  }
  __syncwarp();
  cluster_arrive();
  if (wid >= 8) {
    reg_dealloc<56>();
    const int t = tid - 256;
    unsigned short craw[5];
#pragma unroll
    for (int i = 0; i < 5; i++) craw[i] = __ldg((const unsigned short*)cvec + min(t + i * 128, DM - 1));
    cluster_wait();
    if (wid == 8 && elect_one()) {
#pragma unroll 1
      for (int s = 0; s < QKV_STAGES; s++) {
        mbar_expect_tx(bFull + 8 * s, QKV_STAGE);
        tma_3d_mc(sW + s * QKV_STAGE + rank * 7168, &tmW, 0, s * 32 + rank * 16, ct * 7, bFull + 8 * s, 3);
      }
      if (gemv && blockIdx.x >= 36) load_slab();
    }
    if (wid == 9 && elect_one()) bulk_prefetch_l2((const uint8_t*)wqkv + (size_t)blockIdx.x * (DM * NQKV * 2 / 128), DM * NQKV * 2 / 128);
    __syncwarp();
    if (gemv) {
#pragma unroll
    for (int i = 0; i < 5; i++) {
      const int k = t + i * 128;
      const float cv = __uint_as_float((uint32_t)craw[i] << 16);
      if (k < DM)
        asm volatile("st.shared.b16 [%0], %1;" ::"r"(sSc + (k >> 3) * 128 + (k & 7) * 2),
                     "h"(__bfloat16_as_ushort(__float2bfloat16(__fdividef(cv, 1.f + __expf(-cv))))) : "memory");
    }
    fence_proxy_async();
    named_bar_sync(1, 128);
    mbar_wait(bSlab, 0);
    __syncwarp();
    float m[16];
    const uint32_t alo = desc_addr(sSc) | (8u << 16), blo = desc_addr(sSlab) | (1u << 16), bhi = 32u | (2u << 30);
    wg_fence();
#pragma unroll 1
    for (int ks = 0; ks < 36; ks += 4) {
#pragma unroll
      for (int i = 0; i < 4; i++) wgmma_ss_n32_tb(m, mk64(alo + (ks + i) * 16, 0u), mk64(blo + (ks + i) * 64, bhi), ks + i);
    }
    wg_commit();
    wg_wait<0>();
    if (t < 4) {
#pragma unroll
      for (int i = 0; i < 8; i++) {
        const float v0 = m[(i >> 1) * 4 + (i & 1)];
        const int idx = blockIdx.x * 32 + (i >> 1) * 8 + 2 * t + (i & 1);
        if (blockIdx.x < 36) {
          st_tagged(&g_modx[idx], __float_as_uint(v0), 1u);
        } else {
          const int sec = idx / DM, col = idx - sec * DM;
          const float v = sec == 3 ? 0.5f * v0 : (sec == 4 ? fmaf(0.5f, v0, 0.5f) : v0);
          const int slot = sec == 2 ? 0 : (sec == 3 ? 2 : (sec == 4 ? 1 : 3));
          ((__nv_bfloat16*)g_coef)[(col >> 1) * 8 + slot * 2 + (col & 1)] = __float2bfloat16(v);
        }
      }
    }
    named_bar_sync(1, 128);
    if (wid == 8 && elect_one()) load_x(2, 3);
    }
    __syncwarp();
    pdl_launch();
    if (wid == 8) {
      int slot = 0; uint32_t ph = 0;
#pragma unroll 1
      for (int s = QKV_STAGES; s < 18; s++) {
        mbar_wait(bEmpty + 8 * slot, ph);
        if (elect_one()) {
          mbar_expect_tx(bFull + 8 * slot, QKV_STAGE);
          tma_3d_mc(sW + slot * QKV_STAGE + rank * 7168, &tmW, 0, s * 32 + rank * 16, ct * 7, bFull + 8 * slot, 3);
        }
        if (++slot == QKV_STAGES) { slot = 0; ph ^= 1; }
      }
    } else {
      const int h0 = (n0 + 1) / DH, h1 = min((n0 + 207) / DH, 3 * NH - 1);
#pragma unroll 1
      for (int i = t - 32; i < (h1 - h0 + 1) * 128; i += 96) {
        const int hh = h0 + (i >> 7), tok = rb * 128 + (i & 127);
        uint8_t* p = g_qkv + (size_t)hh * HEAD_BYTES + (tok >> 3) * 384 + 256 + (tok & 7) * 16;
        const bool kflag = hh >= NH && hh < 2 * NH && att_poly_block(tok >> 3);
        *(uint32_t*)(p + 4) = hh >= 2 * NH ? 0x00003F80u : (kflag ? 0x3F803F80u : 0u);
        *(uint2*)(p + 8) = make_uint2(kflag ? 0x00003F80u : 0u, 0u);
      }
    }
  } else {
    const int srow = rb * 128 + ct * 16 + wid * 2;
    const uint32_t* px = (const uint32_t*)(x + (size_t)srow * DM) + lane;
    uint32_t xv[18];
#pragma unroll
    for (int j = 0; j < 18; j++) xv[j] = __ldg(px + j * 32);
    float s[2] = {0.f, 0.f}, q[2] = {0.f, 0.f};
#pragma unroll
    for (int j = 0; j < 18; j++) {
      const float a = bf_lo(xv[j]), b = bf_hi(xv[j]);
      s[j / 9] += a + b;
      q[j / 9] = fmaf(a, a, fmaf(b, b, q[j / 9]));
    }
    float sa = lane < 16 ? s[0] : s[1], so = lane < 16 ? s[1] : s[0];
    float qa = lane < 16 ? q[0] : q[1], qo = lane < 16 ? q[1] : q[0];
    sa += __shfl_xor_sync(0xffffffffu, so, 16);
    qa += __shfl_xor_sync(0xffffffffu, qo, 16);
#pragma unroll
    for (int o = 8; o > 0; o >>= 1) { sa += __shfl_xor_sync(0xffffffffu, sa, o); qa += __shfl_xor_sync(0xffffffffu, qa, o); }
    if ((lane & 15) == 0) {
      const float mu = sa * (1.f / DM), var = fmaxf(fmaf(-mu, mu, qa * (1.f / DM)), 0.f);
      const uint32_t rs = __float_as_uint(rsqrtf(var + 1e-5f));
      st_tagged(&g_stat[srow + (lane >> 4)], __float_as_uint(mu), rs ? rs : 1u);
    }
    __syncwarp();
    cluster_wait();
    if (blockIdx.x < 36 && wid == 7) {
      mbar_wait(bSlab, 0);
      if (elect_one()) load_x(0, 2);
      __syncwarp();
    }
    pdl_launch();
    if (tid < 112) {
      const int jj = tid >> 2, c = tid & 3, n = n0 + jj * 8 + 2 * c, hh = n / DH, d = n - hh * DH;
      asm volatile("st.shared.u32 [%0], %1;" ::"r"(sOff + (((jj >> 2) * 4 + c) * 4 + (jj & 3)) * 4),
                   "r"(hh * HEAD_BYTES + (d >> 3) * 128 + (d & 7) * 2) : "memory");
    }
    if (tid < 36) {
#pragma unroll 1
      for (uint32_t n = 0; n < (1u << 20); n++) {
        if ((ld_tagged(&g_modx[tid * 32 + 31]) >> 32) != 0) break;
        __nanosleep(40);
      }
    }
    named_bar_sync(2, 256);
    {
      unsigned long long m[4], e;
      const unsigned long long* pe = tid < 128 ? &g_modx[1024 + tid] : &g_stat[rb * 128 + tid - 128];
#pragma unroll 1
      for (uint32_t n = 0; n < (1u << 20); n++) {
#pragma unroll
        for (int i = 0; i < 4; i++) m[i] = ld_tagged(&g_modx[tid + 256 * i]);
        e = ld_tagged(pe);
        if ((m[0] >> 32) != 0 && (m[1] >> 32) != 0 && (m[2] >> 32) != 0 && (m[3] >> 32) != 0 && (e >> 32) != 0) break;
        __nanosleep(100);
      }
      auto put = [&](int i, unsigned long long v64) {
        const int k = i < DM ? i : i - DM;
        const float v = __uint_as_float((uint32_t)v64) + (i < DM ? 0.f : 1.f);
        const uint32_t dst = sTab + ((k >> 4) * 4 + ((k & 7) >> 1)) * 16 + ((k >> 3) & 1) * 4 + (k & 1) * 2 + (i < DM ? 8 : 0);
        asm volatile("st.shared.b16 [%0], %1;" ::"r"(dst), "h"(__bfloat16_as_ushort(__float2bfloat16(v))) : "memory");
      };
#pragma unroll
      for (int i = 0; i < 4; i++) put(tid + 256 * i, m[i]);
      if (tid < 128) {
        put(1024 + tid, e);
      } else {
        const float rs = __uint_as_float((uint32_t)(e >> 32));
        const uint32_t r2 = pack_bf16(rs, rs);
        const float nm = -__uint_as_float((uint32_t)e) * bf_lo(r2);
        asm volatile("st.shared.v2.u32 [%0], {%1, %2};" ::"r"(sRow + (tid - 128) * 8), "r"(r2), "r"(pack_bf16(nm, nm)) : "memory");
      }
    }
    named_bar_sync(2, 256);
    __syncwarp();
    reg_alloc<224>();

    float acc[112];
    const int arow = wid * 16 + (lane & 15);
    const uint32_t aBase = sA + arow * 128, aX = arow & 7, aHi = lane >> 4;
    const uint32_t tabBase = sTab + (lane & 3) * 16;
    uint32_t r0, m0, r1, m1;
    asm volatile("ld.shared.v2.u32 {%0, %1}, [%2];" : "=r"(r0), "=r"(m0) : "r"(sRow + (wid * 16 + (lane >> 2)) * 8));
    asm volatile("ld.shared.v2.u32 {%0, %1}, [%2];" : "=r"(r1), "=r"(m1) : "r"(sRow + (wid * 16 + (lane >> 2) + 8) * 8));
    const uint32_t wlo0 = desc_addr(sW) | (64u << 16);
    const uint32_t whi = 32u | (2u << 30);
    const uint32_t remoteEmpty = mapa(bEmpty, rank ^ 1);
    auto load_frag = [&](int ks, uint32_t (&a)[4]) {
      ldmatrix_x4(aBase + (ks >> 2) * 16384 + (((((ks & 3) << 1) | aHi) ^ aX) << 4), a[0], a[1], a[2], a[3]);
      const uint4 cf = lds128(tabBase + ks * 64);
      a[0] = hfma2_bf16(hfma2_bf16(a[0], r0, m0), cf.x, cf.z); a[1] = hfma2_bf16(hfma2_bf16(a[1], r1, m1), cf.x, cf.z);
      a[2] = hfma2_bf16(hfma2_bf16(a[2], r0, m0), cf.y, cf.w); a[3] = hfma2_bf16(hfma2_bf16(a[3], r1, m1), cf.y, cf.w);
    };
    uint32_t fa[4], fb[4], fc[4], fd[4];
    int slot = 0; uint32_t ph = 0;
    int pslot = 0;
    auto release = [&](int s) {
      if ((tid & 127) == 0) { mbar_arrive(bEmpty + 8 * s); mbar_arrive_cluster(remoteEmpty + 8 * s); }
    };
#pragma unroll 1
    for (int s2 = 0; s2 < 9; s2++) {
      if (s2 % 3 == 0) mbar_wait(bA + 8 * (s2 / 3), 0);
      load_frag(4 * s2, fa); load_frag(4 * s2 + 1, fb);
      mbar_wait(bFull + 8 * slot, ph);
      wg_fence();
      wgmma_rs_n224_tb(acc, fa[0], fa[1], fa[2], fa[3], mk64(wlo0 + slot * (QKV_STAGE >> 4), whi), s2);
      wgmma_rs_n224_tb(acc, fb[0], fb[1], fb[2], fb[3], mk64(wlo0 + slot * (QKV_STAGE >> 4) + 448, whi), 1);
      wg_commit();
      wg_wait<1>();
      if (s2 > 0 && s2 < 7) release(pslot);
      pslot = slot;
      if (++slot == QKV_STAGES) { slot = 0; ph ^= 1; }
      load_frag(4 * s2 + 2, fc); load_frag(4 * s2 + 3, fd);
      mbar_wait(bFull + 8 * slot, ph);
      wg_fence();
      wgmma_rs_n224_tb(acc, fc[0], fc[1], fc[2], fc[3], mk64(wlo0 + slot * (QKV_STAGE >> 4), whi), 1);
      wgmma_rs_n224_tb(acc, fd[0], fd[1], fd[2], fd[3], mk64(wlo0 + slot * (QKV_STAGE >> 4) + 448, whi), 1);
      wg_commit();
      wg_wait<1>();
      if (s2 < 7) release(pslot);
      pslot = slot;
      if (++slot == QKV_STAGES) { slot = 0; ph ^= 1; }
    }
    wg_wait<0>();

    const int trow = rb * 128 + wid * 16 + (lane >> 2);
    const uint32_t rowOff = (trow >> 3) * 384 + (trow & 7) * 16;
#pragma unroll
    for (int jq = 0; jq < 7; jq++) {
      const uint4 o4 = lds128(sOff + (jq * 4 + (lane & 3)) * 16);
      const uint32_t off[4] = {o4.x, o4.y, o4.z, o4.w};
#pragma unroll
      for (int i = 0; i < 4; i++) {
        const int jj = jq * 4 + i;
        uint8_t* p = g_qkv + (rowOff + off[i]);
        *(uint32_t*)p = pack_bf16(acc[4 * jj], acc[4 * jj + 1]);
        *(uint32_t*)(p + 384) = pack_bf16(acc[4 * jj + 2], acc[4 * jj + 3]);
      }
    }
  }
}

constexpr int ATT_K = 0, ATT_V = HEAD_BYTES, ATT_Q = 2 * HEAD_BYTES, ATT_PART = ATT_Q + 64 * 384,
              ATT_RED = ATT_PART + 2 * 5120, ATT_BAR = ATT_RED + 64, ATT_SMEM = ATT_BAR + 256 + 128;
constexpr float ATT_BOUND2 = 50.f * 50.f * 0.9f, ATT_VBOUND2 = 1e30f;

__device__ __forceinline__ uint32_t exp2_pair_mufu(float a, float b) { return pack_bf16(ex2(a), ex2(b)); }
__device__ __forceinline__ uint32_t exp2_pair_fma(float a, float b, uint32_t c6400) {
  const uint32_t w = __byte_perm(__float_as_uint(a), __float_as_uint(b), 0x5410);
  uint32_t u, t, g;
  asm("lop3.b32 %0, %1, 0x007F007F, %2, 0xEA;" : "=r"(u) : "r"(w), "r"(c6400));
  asm("fma.rn.f16x2 %0, %1, %2, %3;" : "=r"(t) : "r"(u), "r"(0x2aac2aacu), "r"(0xd318d318u));
  asm("fma.rn.f16x2 %0, %1, %1, %2;" : "=r"(g) : "r"(t), "r"(0x64746475u));
  return w + g;
}

__device__ __forceinline__ void attn_store(const float (&o)[12], __nv_bfloat16* o_out, int row, int head, int lane) {
  const float l0 = __shfl_sync(0xffffffffu, o[8], (lane & ~3) | 1), l1 = __shfl_sync(0xffffffffu, o[10], (lane & ~3) | 1);
  const float i0 = __fdividef(1.f, l0), i1 = __fdividef(1.f, l1);
  const int c = lane & 3;
  uint32_t* po = (uint32_t*)(o_out + (size_t)row * DM + head * DH + 2 * c);
  po[0] = pack_bf16(o[0] * i0, o[1] * i0);
  po[4] = pack_bf16(o[4] * i0, o[5] * i0);
  po[8 * 288] = pack_bf16(o[2] * i1, o[3] * i1);
  po[8 * 288 + 4] = pack_bf16(o[6] * i1, o[7] * i1);
  if (c == 0) {
    po[8] = pack_bf16(o[8] * i0, o[9] * i0);
    po[8 * 288 + 8] = pack_bf16(o[10] * i1, o[11] * i1);
  }
}

constexpr float QSCALE = 0.23570226039551584f * 1.4426950408889634f;
constexpr uint32_t ATT_MAGIC = 0xC29447C0u, ATT_HALF = 0x00003B80u;
__device__ __forceinline__ uint32_t scale_bf16x2(uint32_t v) { return pack_bf16(bf_lo(v) * QSCALE, bf_hi(v) * QSCALE); }
__device__ __forceinline__ float sumsq_bf16x2(uint32_t v) { const float a = bf_lo(v), b = bf_hi(v); return fmaf(a, a, b * b); }

__global__ void __launch_bounds__(512, 1)
attn_kernel(const uint8_t* __restrict__ qkv, __nv_bfloat16* __restrict__ o_out, const uint8_t* __restrict__ pf0, uint32_t pf0_bytes,
            const uint8_t* __restrict__ pf1, const uint8_t* __restrict__ pf2, uint32_t pf_bytes, uint32_t c6400) {
  extern __shared__ uint8_t smem_raw[];
  const uint32_t sb = (smem_u32(smem_raw) + 127) & ~127u;
  const uint32_t sK = sb + ATT_K, sV = sb + ATT_V, sQ = sb + ATT_Q, sPart = sb + ATT_PART, sRed = sb + ATT_RED;
  const uint32_t bars = sb + ATT_BAR, bQ = bars + 8 * 16, bPart = bars + 8 * 17, bChk = bars + 8 * 19, bQ2 = bars + 8 * 20;
  auto chunk_bar = [&](int c) { return bars + 8 * c; };
  const int tid = threadIdx.x, lane = tid & 31, wg = __shfl_sync(0xffffffffu, tid >> 7, 0), warp = (tid >> 5) & 3;
  const int head = blockIdx.x >> 2, qq = blockIdx.x & 3;
  if (tid == 0) {
    for (int i = 0; i < 16; i++) mbar_init(bars + 8 * i, 1);
    mbar_init(bQ, 1); mbar_init(bQ2, 1);
    mbar_init(bPart, 128); mbar_init(bPart + 8, 128); mbar_init(bChk, 12);
    fence_mbar_init();
    asm volatile("st.shared.v2.u32 [%0], {%1, %1};" ::"r"(sRed), "r"(0u) : "memory");
  }
  __syncthreads();
  const uint32_t k0lo = desc_addr(sK) | (8u << 16), k1lo = desc_addr(sK + 256), khi = 24;
  const uint32_t vlo = desc_addr(sV) | (24u << 16), vhi = 8;
  const uint32_t zero = c6400 ^ 0x64006400u;
  const int ubeg = wg * 43, uend = wg == 2 ? 128 : ubeg + 43;

  uint32_t qa0 = zero, qa1 = zero, qa2 = zero, qa3 = zero, qb0 = zero, qb1 = zero;
  const uint32_t qz0 = zero, qz1 = c6400 - 0x64006400u;
  float qmax = 0.f;
  auto load_q = [&](int tile, bool fast) {
    const uint32_t qs = sQ + (tile * 8 + warp * 2) * 384 + lane * 4;
    qa0 = lds32(qs); qa1 = lds32(qs + 384); qa2 = lds32(qs + 128); qa3 = lds32(qs + 384 + 128);
    qb0 = lds32(qs + 256); qb1 = lds32(qs + 384 + 256);
    qa0 = scale_bf16x2(qa0); qa1 = scale_bf16x2(qa1); qa2 = scale_bf16x2(qa2); qa3 = scale_bf16x2(qa3);
    qb0 = scale_bf16x2(qb0); qb1 = scale_bf16x2(qb1);
    float n0 = sumsq_bf16x2(qa0) + sumsq_bf16x2(qa2) + sumsq_bf16x2(qb0);
    float n1 = sumsq_bf16x2(qa1) + sumsq_bf16x2(qa3) + sumsq_bf16x2(qb1);
    if (fast && (lane & 3) == 1) { qb0 = ATT_MAGIC; qb1 = ATT_MAGIC; }
    if (fast && (lane & 3) == 2) { qb0 = ATT_HALF; qb1 = ATT_HALF; }
    n0 += __shfl_xor_sync(0xffffffffu, n0, 1); n1 += __shfl_xor_sync(0xffffffffu, n1, 1);
    n0 += __shfl_xor_sync(0xffffffffu, n0, 2); n1 += __shfl_xor_sync(0xffffffffu, n1, 2);
    const float m = (n0 > n1 || n0 != n0) ? n0 : n1;
    qmax = (m > qmax || m != m) ? m : qmax;
  };

  if (wg == 3) {
    reg_dealloc<32>();
    if (warp != 0) return;
    const uint8_t* gQ = qkv + (size_t)head * HEAD_BYTES + qq * 64 * 384;
    const uint8_t* gK = qkv + (size_t)(NH + head) * HEAD_BYTES;
    const uint8_t* gV = qkv + (size_t)(2 * NH + head) * HEAD_BYTES;
    pdl_wait();
    pdl_launch();
    auto load_chunk = [&](int c) {
      mbar_expect_tx(bars + 8 * c, 12288);
      bulk_g2s(sK + c * 6144, gK + c * 6144, 6144, bars + 8 * c);
      bulk_g2s(sV + c * 6144, gV + c * 6144, 6144, bars + 8 * c);
    };
    if (elect_one()) {
      mbar_expect_tx(bQ, 3 * 3072);
      bulk_g2s(sQ, gQ, 3072, bQ);
      bulk_g2s(sQ + 2 * 3072, gQ + 2 * 3072, 3072, bQ);
      bulk_g2s(sQ + 5 * 3072, gQ + 5 * 3072, 3072, bQ);
      load_chunk(0); load_chunk(11); load_chunk(6);
    }
    mbar_wait(bars, 0);
    if (elect_one()) {
#pragma unroll 1
      for (int i = 1; i < 5; i++) { load_chunk(i); load_chunk(11 + i); load_chunk(6 + i); }
      load_chunk(5);
      mbar_expect_tx(bQ2, 5 * 3072);
      bulk_g2s(sQ + 3072, gQ + 3072, 3072, bQ2);
      bulk_g2s(sQ + 3 * 3072, gQ + 3 * 3072, 2 * 3072, bQ2);
      bulk_g2s(sQ + 6 * 3072, gQ + 6 * 3072, 2 * 3072, bQ2);
      const uint32_t per = pf_bytes / 128;
#pragma unroll 1
      for (uint32_t o2 = 0; o2 < per; o2 += 8192) {
        bulk_prefetch_l2(pf1 + (size_t)blockIdx.x * per + o2, min(8192u, per - o2));
        bulk_prefetch_l2(pf2 + (size_t)blockIdx.x * per + o2, min(8192u, per - o2));
      }
      bulk_prefetch_l2(pf0 + (size_t)blockIdx.x * (pf0_bytes / 128), pf0_bytes / 128);
    }
    __syncwarp();
    if (lane < 16) g_stat[blockIdx.x * 16 + lane] = 0ull;
    else if (lane < 25) g_modx[blockIdx.x * 9 + lane - 16] = 0ull;
    float4* z = (float4*)g_red + (size_t)blockIdx.x * 2304 + lane;
#pragma unroll 8
    for (int i = 0; i < 72; i++) z[i * 32] = make_float4(0.f, 0.f, 0.f, 0.f);
    if (blockIdx.x == 0) g_cnt[lane] = 0;
    return;
  }
  reg_alloc<160>();

  const int nseg = wg == 0 ? 3 : (wg == 1 ? 4 : 3);
#pragma unroll 1
  for (int seg = -1; seg < nseg; seg++) {
    const int tile = (ubeg >> 4) + max(seg, 0);
    const int c0 = __shfl_sync(0xffffffffu, seg <= 0 ? (ubeg & 15) : 0, 0);
    const int c1 = __shfl_sync(0xffffffffu, seg < 0 ? c0 + 1 : min(16, uend - tile * 16), 0);
    float s[64], o[12];
    uint32_t pk[32];
    if (seg > 0) mbar_wait(bQ2, 0);
    load_q(tile, true);
    if (seg < 0) qmax = 0.f;
    if (seg >= 0) {
      mbar_wait(chunk_bar(c0), 0);
      __syncwarp();
    }
    wg_fence();
    wgmma_rs_n128_init(s, qa0, qa1, qa2, qa3, mk64(k0lo + c0 * 384, khi));
    wgmma_rs_n128(s, qb0, qb1, qz0, qz1, mk64(k1lo + c0 * 384, khi), 1);
    wg_commit();
#pragma unroll 1
    for (int j = c0; j < c1; j++) {
      const int jn = min(j + 1, c1 - 1);
      const bool rdy = mbar_test(chunk_bar(jn), 0) | (seg < 0);
      wg_wait<0>();
#pragma unroll
      for (int i = 0; i < 32; i++)
        pk[i] = att_poly_block(i >> 1) ? exp2_pair_fma(s[2 * i], s[2 * i + 1], c6400) : exp2_pair_mufu(s[2 * i], s[2 * i + 1]);
      if (!rdy) mbar_wait(chunk_bar(jn), 0);
      wg_fence();
#pragma unroll
      for (int kk = 0; kk < 8; kk++)
        wgmma_rs_n24_tb(o, pk[4 * kk], pk[4 * kk + 1], pk[4 * kk + 2], pk[4 * kk + 3], mk64(vlo + j * 384 + kk * 48, vhi), kk ? 1 : j - c0);
      wgmma_rs_n128_init(s, qa0, qa1, qa2, qa3, mk64(k0lo + jn * 384, khi));
      wgmma_rs_n128(s, qb0, qb1, qz0, qz1, mk64(k1lo + jn * 384, khi), 1);
      wg_commit();
    }
    wg_wait<0>();
    if (seg < 0) {
      mbar_wait(bQ, 0);
      continue;
    }
    const uint32_t pslot = (tid & 127) * 16, pext = 4096 + (((tid & 127) >> 2) * 2 + (lane & 1)) * 16;
    if (c0 != 0) {
      const uint32_t p = sPart + (wg - 1) * 5120;
      sts128(p + pslot, __float_as_uint(o[0]), __float_as_uint(o[1]), __float_as_uint(o[2]), __float_as_uint(o[3]));
      sts128(p + pslot + 2048, __float_as_uint(o[4]), __float_as_uint(o[5]), __float_as_uint(o[6]), __float_as_uint(o[7]));
      if ((lane & 3) < 2)
        sts128(p + pext, __float_as_uint(o[8]), __float_as_uint(o[9]), __float_as_uint(o[10]), __float_as_uint(o[11]));
      mbar_arrive(bPart + 8 * (wg - 1));
    } else {
      if (c1 != 16) {
        mbar_wait(bPart + 8 * wg, 0);
        const uint32_t p = sPart + wg * 5120;
        const uint4 a = lds128(p + pslot), b = lds128(p + pslot + 2048), c = lds128(p + pext);
        o[0] += __uint_as_float(a.x); o[1] += __uint_as_float(a.y); o[2] += __uint_as_float(a.z); o[3] += __uint_as_float(a.w);
        o[4] += __uint_as_float(b.x); o[5] += __uint_as_float(b.y); o[6] += __uint_as_float(b.z); o[7] += __uint_as_float(b.w);
        o[8] += __uint_as_float(c.x); o[9] += __uint_as_float(c.y); o[10] += __uint_as_float(c.z); o[11] += __uint_as_float(c.w);
      }
      attn_store(o, o_out, qq * 512 + tile * 64 + warp * 16 + (lane >> 2), head, lane);
    }
    if (seg == 1) {
      float kmax = 0.f, vmax = 0.f;
#pragma unroll 1
      for (int key = tid; key < SEQ; key += 384) {
        const uint32_t off = (key >> 3) * 384 + (key & 7) * 16;
        float n2[2];
#pragma unroll
        for (int m = 0; m < 2; m++) {
          const uint32_t base = (m ? sV : sK) + off;
          const uint4 a = lds128(base), b = lds128(base + 128);
          uint32_t acc = hfma2_bf16(a.x, a.x, zero);
          acc = hfma2_bf16(a.y, a.y, acc); acc = hfma2_bf16(a.z, a.z, acc); acc = hfma2_bf16(a.w, a.w, acc);
          acc = hfma2_bf16(b.x, b.x, acc); acc = hfma2_bf16(b.y, b.y, acc); acc = hfma2_bf16(b.z, b.z, acc);
          acc = hfma2_bf16(b.w, b.w, acc);
          const uint32_t c = lds32(base + 256);
          acc = hfma2_bf16(c, c, acc);
          n2[m] = bf_lo(acc) + bf_hi(acc);
        }
        kmax = (n2[0] > kmax || n2[0] != n2[0]) ? n2[0] : kmax;
        vmax = (n2[1] > vmax || n2[1] != n2[1]) ? n2[1] : vmax;
      }
      const uint32_t km = __reduce_max_sync(0xffffffffu, __float_as_uint(kmax) & 0x7fffffffu);
      const uint32_t vm = __reduce_max_sync(0xffffffffu, __float_as_uint(vmax) & 0x7fffffffu);
      if (lane == 0) {
        asm volatile("red.shared.max.u32 [%0], %1;" ::"r"(sRed), "r"(km) : "memory");
        asm volatile("red.shared.max.u32 [%0], %1;" ::"r"(sRed + 4), "r"(vm) : "memory");
        mbar_arrive(bChk);
      }
    }
  }

  {
    mbar_wait(bChk, 0);
    const float kk2 = __uint_as_float(lds32(sRed)), vv2 = __uint_as_float(lds32(sRed + 4));
    const uint32_t bad = !(qmax * kk2 <= ATT_BOUND2 && vv2 <= ATT_VBOUND2);
    uint32_t any;
    asm volatile("{\n.reg .pred p, q;\nsetp.ne.u32 p, %1, 0;\nbar.red.or.pred q, %2, 128, p;\nselp.u32 %0, 1, 0, q;\n}"
                 : "=r"(any) : "r"(bad), "r"(1 + wg) : "memory");
    if (!any) return;
  }

#pragma unroll 1
  for (int tile = wg * 3; tile < min(wg * 3 + 3, 8); tile++) {
    load_q(tile, false);
    float s2[64], o2[12];
    uint32_t p2[32];
    float m0 = -INFINITY, m1 = -INFINITY;
#pragma unroll 1
    for (int j = 0; j < 16; j++) {
      wg_fence();
      wgmma_rs_n128_init(s2, qa0, qa1, qa2, qa3, mk64(k0lo + j * 384, khi));
      wgmma_rs_n128(s2, qb0, qb1, qz0, qz1, mk64(k1lo + j * 384, khi), 1);
      wg_commit();
      wg_wait<0>();
#pragma unroll
      for (int i = 0; i < 16; i++) {
        m0 = fmaxf(m0, fmaxf(s2[4 * i], s2[4 * i + 1]));
        m1 = fmaxf(m1, fmaxf(s2[4 * i + 2], s2[4 * i + 3]));
      }
    }
    m0 = fmaxf(m0, __shfl_xor_sync(0xffffffffu, m0, 1)); m1 = fmaxf(m1, __shfl_xor_sync(0xffffffffu, m1, 1));
    m0 = fmaxf(m0, __shfl_xor_sync(0xffffffffu, m0, 2)); m1 = fmaxf(m1, __shfl_xor_sync(0xffffffffu, m1, 2));
#pragma unroll 1
    for (int j = 0; j < 16; j++) {
      wg_fence();
      wgmma_rs_n128_init(s2, qa0, qa1, qa2, qa3, mk64(k0lo + j * 384, khi));
      wgmma_rs_n128(s2, qb0, qb1, qz0, qz1, mk64(k1lo + j * 384, khi), 1);
      wg_commit();
      wg_wait<0>();
#pragma unroll
      for (int i = 0; i < 16; i++) {
        p2[2 * i] = exp2_pair_mufu(s2[4 * i] - m0, s2[4 * i + 1] - m0);
        p2[2 * i + 1] = exp2_pair_mufu(s2[4 * i + 2] - m1, s2[4 * i + 3] - m1);
      }
      wg_fence();
#pragma unroll
      for (int kk = 0; kk < 8; kk++)
        wgmma_rs_n24_tb(o2, p2[4 * kk], p2[4 * kk + 1], p2[4 * kk + 2], p2[4 * kk + 3], mk64(vlo + j * 384 + kk * 48, vhi), kk ? 1 : j);
      wg_commit();
      wg_wait<0>();
    }
    attn_store(o2, o_out, qq * 512 + tile * 64 + warp * 16 + (lane >> 2), head, lane);
  }
}

constexpr int PRJ_STAGES = 6;
constexpr int PRJ_A = 0, PRJ_B = 9 * 8192, PRJ_STAT = PRJ_B + PRJ_STAGES * 24576, PRJ_BAR = PRJ_STAT + 64 * 9 * 8,
              PRJ_SMEM = PRJ_BAR + 256 + 1024;

__global__ void __launch_bounds__(416, 1)
proj_kernel(const __grid_constant__ CUtensorMap tmO, const __grid_constant__ CUtensorMap tmWo, const __grid_constant__ CUtensorMap tmX1,
            const __grid_constant__ CUtensorMap tmH2, const __grid_constant__ CUtensorMap tmX) {
  extern __shared__ uint8_t smem_raw[];
  const uint32_t sb = (smem_u32(smem_raw) + 1023) & ~1023u;
  const uint32_t sA = sb + PRJ_A, sB = sb + PRJ_B, sStat = sb + PRJ_STAT;
  const uint32_t bA = sb + PRJ_BAR, bFull = bA + 8 * 9, bEmpty = bFull + 8 * PRJ_STAGES, bStat = bEmpty + 8 * PRJ_STAGES, bX = bStat + 8;
  const int tid = threadIdx.x, lane = tid & 31, wid = __shfl_sync(0xffffffffu, tid >> 5, 0);
  const uint32_t nt = cluster_rank();
  const int rb = blockIdx.x / 3;
  if (tid == 32) { prefetch_tmap(&tmWo); prefetch_tmap(&tmO); prefetch_tmap(&tmX); prefetch_tmap(&tmX1); prefetch_tmap(&tmH2); }
  if (tid == 0) {
    for (int i = 0; i < 9; i++) mbar_init(bA + 8 * i, 1);
    for (int i = 0; i < PRJ_STAGES; i++) { mbar_init(bFull + 8 * i, 1); mbar_init(bEmpty + 8 * i, 3); }
    mbar_init(bStat, 1);
    mbar_init(bX, 1);
    mbar_expect_tx(bStat, 64 * 9 * 8);
    fence_mbar_init();
  }
  cluster_arrive();
  cluster_wait();

  if (wid == 12) {
    if (elect_one()) {
#pragma unroll
      for (int kt = 0; kt < PRJ_STAGES; kt++) {
        mbar_expect_tx(bFull + 8 * kt, 24576);
#pragma unroll
        for (int w = 0; w < 3; w++) tma_2d(sB + kt * 24576 + w * 8192, &tmWo, nt * 192 + w * 64, kt * 64, bFull + 8 * kt);
      }
    }
    pdl_wait();
    pdl_launch();
    if (elect_one()) {
#pragma unroll
      for (int kt = 0; kt < 9; kt++) mbar_expect_tx(bA + 8 * kt, 8192);
#pragma unroll
      for (int i = 0; i < 3; i++) tma_2d_mc(sA + (nt + 3 * i) * 8192, &tmO, (nt + 3 * i) * 64, rb * 64, bA + 8 * (nt + 3 * i), 7);
    }
#pragma unroll
    for (int kt = PRJ_STAGES; kt < 9; kt++) {
      const int s = kt - PRJ_STAGES;
      mbar_wait(bEmpty + 8 * s, 0);
      if (elect_one()) {
        mbar_expect_tx(bFull + 8 * s, 24576);
#pragma unroll
        for (int w = 0; w < 3; w++) tma_2d(sB + s * 24576 + w * 8192, &tmWo, nt * 192 + w * 64, kt * 64, bFull + 8 * s);
      }
    }
    if (elect_one()) {
      mbar_expect_tx(bX, 3 * 8192);
#pragma unroll
      for (int w = 0; w < 3; w++) tma_2d(sA + w * 8192, &tmX, nt * 192 + w * 64, rb * 64, bX);
    }
    return;
  }
  const int w = __shfl_sync(0xffffffffu, wid >> 2, 0), warp = wid & 3, c = lane & 3;
  const int col0 = nt * 192 + w * 64 + 2 * c;
  uint32_t xr[16];
  uint4 cf[8];
#pragma unroll
  for (int jj = 0; jj < 8; jj++) cf[jj] = __ldcg(&g_coef[(col0 >> 1) + jj * 4]);
  float acc[32];
  const uint32_t alo = desc_addr(sA) | (1u << 16), ahi = 64u | (1u << 30);
  const uint32_t blo = desc_addr(sB + w * 8192) | (512u << 16), bhi = 64u | (1u << 30);
  auto k_tile = [&](int kt) {
    const int s = kt < PRJ_STAGES ? kt : kt - PRJ_STAGES;
    mbar_wait(bA + 8 * kt, 0);
    mbar_wait(bFull + 8 * s, kt < PRJ_STAGES ? 0 : 1);
    wg_fence();
#pragma unroll
    for (int kk = 0; kk < 4; kk++)
      wgmma_ss_n64_tb(acc, mk64(alo + kt * 512 + kk * 2, ahi), mk64(blo + s * 1536 + kk * 128, bhi), kk ? 1 : kt);
    wg_commit();
  };
#pragma unroll 1
  for (int kt = 0; kt < 9; kt++) {
    k_tile(kt);
    if (kt >= 1 && kt <= 3) {
      wg_wait<1>();
      if ((tid & 127) == 0) mbar_arrive(bEmpty + 8 * (kt - 1));
    }
  }
  wg_wait<0>();

  mbar_wait(bX, 0);
  load_frag_tile(sA + w * 8192, warp * 16, lane, xr);
  float s0 = 0.f, s1 = 0.f, q0 = 0.f, q1 = 0.f;
#pragma unroll
  for (int jj = 0; jj < 8; jj++) {
    const uint32_t p0 = hfma2_bf16(cf[jj].x, pack_bf16(acc[4 * jj], acc[4 * jj + 1]), xr[2 * jj]);
    const uint32_t p1 = hfma2_bf16(cf[jj].x, pack_bf16(acc[4 * jj + 2], acc[4 * jj + 3]), xr[2 * jj + 1]);
    xr[2 * jj] = p0; xr[2 * jj + 1] = p1;
    float a = bf_lo(p0), b = bf_hi(p0);
    s0 += a + b; q0 = fmaf(a, a, fmaf(b, b, q0));
    a = bf_lo(p1); b = bf_hi(p1);
    s1 += a + b; q1 = fmaf(a, a, fmaf(b, b, q1));
  }
  s0 += __shfl_xor_sync(0xffffffffu, s0, 1); s1 += __shfl_xor_sync(0xffffffffu, s1, 1);
  q0 += __shfl_xor_sync(0xffffffffu, q0, 1); q1 += __shfl_xor_sync(0xffffffffu, q1, 1);
  s0 += __shfl_xor_sync(0xffffffffu, s0, 2); s1 += __shfl_xor_sync(0xffffffffu, s1, 2);
  q0 += __shfl_xor_sync(0xffffffffu, q0, 2); q1 += __shfl_xor_sync(0xffffffffu, q1, 2);
  const int rl = warp * 16 + (lane >> 2);
  const uint32_t stg = sB + w * 8192;
  store_frag_tile(stg, warp * 16, lane, xr);
  fence_proxy_async();
  if (c < 3) {
    const uint32_t dst = mapa(sStat + (rl * 9 + nt * 3 + w) * 8, c), bar = mapa(bStat, c);
    asm volatile("st.async.weak.shared::cluster.mbarrier::complete_tx::bytes.v2.f32 [%0], {%1, %2}, [%3];"
                 ::"r"(dst), "f"(s0), "f"(q0), "r"(bar) : "memory");
    asm volatile("st.async.weak.shared::cluster.mbarrier::complete_tx::bytes.v2.f32 [%0], {%1, %2}, [%3];"
                 ::"r"(dst + 8 * 72), "f"(s1), "f"(q1), "r"(bar) : "memory");
  }
  if (w == 0) named_bar_sync(1, 128); else if (w == 1) named_bar_sync(2, 128); else named_bar_sync(3, 128);
  if (warp == 0 && elect_one()) {
    tma_store_2d(&tmX1, stg, nt * 192 + w * 64, rb * 64);
    bulk_commit();
  }
  __syncwarp();
  mbar_wait(bStat, 0);
  uint32_t rs2[2], nm2[2];
#pragma unroll
  for (int h = 0; h < 2; h++) {
    float sm = 0.f, sq = 0.f;
#pragma unroll
    for (int i = 0; i < 9; i++) {
      float2 v;
      asm volatile("ld.shared.v2.f32 {%0, %1}, [%2];" : "=f"(v.x), "=f"(v.y) : "r"(sStat + ((rl + 8 * h) * 9 + i) * 8));
      sm += v.x; sq += v.y;
    }
    const float mu = sm * (1.f / DM), rstd = rsqrtf(fmaxf(fmaf(-mu, mu, sq * (1.f / DM)), 0.f) + 1e-5f);
    rs2[h] = pack_bf16(rstd, rstd);
    const float nm = -mu * bf_lo(rs2[h]);
    nm2[h] = pack_bf16(nm, nm);
  }
#pragma unroll
  for (int jj = 0; jj < 8; jj++) {
    xr[2 * jj] = hfma2_bf16(hfma2_bf16(xr[2 * jj], rs2[0], nm2[0]), cf[jj].y, cf[jj].z);
    xr[2 * jj + 1] = hfma2_bf16(hfma2_bf16(xr[2 * jj + 1], rs2[1], nm2[1]), cf[jj].y, cf[jj].z);
  }
  store_frag_tile(stg + 24576, warp * 16, lane, xr);
  fence_proxy_async();
  if (w == 0) named_bar_sync(1, 128); else if (w == 1) named_bar_sync(2, 128); else named_bar_sync(3, 128);
  if (warp == 0 && elect_one()) {
    tma_store_2d(&tmH2, stg + 24576, nt * 192 + w * 64, rb * 64);
    bulk_commit();
    bulk_wait_read();
  }
}

constexpr int FFN_STAGES = 5, FFN_STAGES2 = 8, FFN_SWITCH = 40;
constexpr int FFN_A = 0, FFN_W = 147456, FFN_BAR = FFN_W + FFN_STAGES * 16384, FFN_SMEM = FFN_BAR + 512 + 1024;
__device__ __forceinline__ uint32_t ffn_slot_off(int slot) { return slot < FFN_STAGES ? FFN_W + slot * 16384 : (slot - 1) * 16384; }

template <int C>
__device__ __forceinline__ void ffn_silu(const float* a, uint32_t (&h)[144]) {
#pragma unroll
  for (int i = 0; i < 16; i++) {
    const float x0 = a[2 * i], x1 = a[2 * i + 1];
    h[16 * C + i] = pack_bf16(fmaf(x0, tanh_approx(x0), x0), fmaf(x1, tanh_approx(x1), x1));
  }
}

struct FfnCtx {
  uint32_t sA, bA, bFull, bEmpty, remoteEmpty, bStgFull, bStgEmpty, bFin, bX;
  int slot, pslot, nslot; uint32_t ph;
  int tid, wg;
  int zero;
};
__device__ __forceinline__ void ffn_release(const FfnCtx& x, int s) {
  if ((x.tid & 127) == 0) { mbar_arrive(x.bEmpty + 8 * s); mbar_arrive_cluster(x.remoteEmpty + 8 * s); }
}
__device__ __forceinline__ void ffn_next(FfnCtx& x, bool release) {
  wg_wait<1>();
  if (release) ffn_release(x, x.pslot);
  x.pslot = x.slot;
  x.ph ^= 1u << x.slot;
  if (++x.slot == x.nslot) x.slot = 0;
}
__device__ __forceinline__ void ffn_wait_full(const FfnCtx& x) { mbar_wait(x.bFull + 8 * x.slot, (x.ph >> x.slot) & 1); }
__device__ __forceinline__ void ffn_order_wait(const FfnCtx& x) { if (x.wg == 1) named_bar_sync(3, 256); }
__device__ __forceinline__ void ffn_order_signal(const FfnCtx& x) { if (x.wg == 0) named_bar_arrive(3, 256); }
constexpr uint32_t FFN_DHI = 64u | (1u << 30);
__device__ __forceinline__ uint32_t ffn_alo(const FfnCtx& x) { return desc_addr(x.sA + x.wg * 8192) | (1u << 16); }
__device__ __forceinline__ uint32_t ffn_blo(const FfnCtx& x) { return desc_addr(x.sA + ffn_slot_off(x.slot)) | (512u << 16); }

template <int P>
__device__ __forceinline__ void ffn_pair(FfnCtx& x, float (&acc)[64], float (&prev)[64], uint32_t (&h)[144]) {
  const uint32_t alo = ffn_alo(x);
  auto stage = [&](int kt, int scale0) {
    if (P == 0) mbar_wait(x.bA + 8 * kt, 0);
    ffn_wait_full(x);
    wg_fence();
    const uint32_t blo = ffn_blo(x);
    wgmma_ss_n128_tb(acc, mk64(alo + kt * 1024, FFN_DHI), mk64(blo, FFN_DHI), scale0);
#pragma unroll
    for (int kk = 1; kk < 4; kk++) wgmma_ss_n128_tb(acc, mk64(alo + kt * 1024 + kk * 2, FFN_DHI), mk64(blo + kk * 128, FFN_DHI), 1);
    wg_commit();
  };
  if (P > 0) ffn_order_wait(x);
  stage(0, x.zero);
  ffn_next(x, P > 0);
  if (P > 0) ffn_silu<(P > 0 ? 2 * P - 2 : 0)>(prev, h);
  stage(1, 1);
  if (P > 0) ffn_order_signal(x);
  ffn_next(x, true);
  if (P > 0) ffn_silu<(P > 0 ? 2 * P - 1 : 0)>(prev + 32, h);
#pragma unroll 1
  for (int kt = 2; kt < 9; kt++) {
    stage(kt, 1);
    ffn_next(x, true);
  }
}

__device__ __forceinline__ float* ffn_red_ptr(int rb, int s, int wg) { return g_red + (size_t)((rb * 9 + s) * 2 + wg) * 4096; }

__device__ __forceinline__ void ffn_stage_partial(const FfnCtx& x, const float (&a)[32], int n) {
  const int b = n & 1;
  mbar_wait(x.bStgEmpty + 8 * (x.wg * 2 + b), ((n >> 1) & 1) ^ 1);
  const uint32_t base = x.sA + b * 32768 + x.wg * 8192 + (x.tid & 127) * 16;
#pragma unroll
  for (int i = 0; i < 8; i++)
    sts128(base + (i >> 2) * 16384 + (i & 3) * 2048, __float_as_uint(a[4 * i]), __float_as_uint(a[4 * i + 1]),
           __float_as_uint(a[4 * i + 2]), __float_as_uint(a[4 * i + 3]));
  fence_proxy_async();
  mbar_arrive(x.bStgFull + 8 * (x.wg * 2 + b));
}

__device__ __forceinline__ uint32_t ffn_x_tile(uint32_t sA, int wg) { return sA + 7 * 16384 + wg * 8192; }
__device__ __forceinline__ uint32_t ffn_sum_tile(uint32_t sA, int wg) { return sA + wg * 8192; }

__device__ __forceinline__ void ffn_finish(const FfnCtx& x, const float (&a)[32], int rb, int fs, int s, const CUtensorMap* tmOut,
                                           __nv_bfloat16* out) {
  const int t = x.tid & 127, lane = t & 31, warp = __shfl_sync(0xffffffffu, t >> 5, 0);
  const uint32_t* pg = (const uint32_t*)(g_coef + (lane & 3)) + 3;
  uint32_t xr[16], gb[8];
#pragma unroll
  for (int jj = 0; jj < 8; jj++) gb[jj] = __ldcg(pg + (s * 32 + jj * 4) * 4);
  if (warp == (fs >> 1)) {
    const int row = rb * 128 + x.wg * 64 + warp * 16 + (lane >> 2) + 8 * (fs & 1), col = 7 * 64 + 2 * (lane & 3);
    const uint32_t* px = (const uint32_t*)(g_x1 + (size_t)row * DM + col);
    uint32_t* po = (uint32_t*)(out + (size_t)row * DM + col);
    uint32_t x7[8], g7[8];
#pragma unroll
    for (int jj = 0; jj < 8; jj++) { x7[jj] = __ldcg(px + jj * 4); g7[jj] = __ldcg(pg + (7 * 32 + jj * 4) * 4); }
    mbar_wait(x.bX + 8 * (x.wg * 2), 0);
    const float2* ps = (const float2*)(ffn_red_ptr(rb, 7, x.wg) + t * 4 + 2 * (fs & 1));
    float2 r7[8];
#pragma unroll
    for (int jj = 0; jj < 8; jj++) r7[jj] = __ldcg(ps + jj * 256);
#pragma unroll
    for (int jj = 0; jj < 8; jj++) po[jj * 4] = hfma2_bf16(g7[jj], pack_bf16(r7[jj].x, r7[jj].y), x7[jj]);
  }
  const uint32_t xt = ffn_x_tile(x.sA, x.wg), st = ffn_sum_tile(x.sA, x.wg) + t * 16;
  mbar_wait(x.bX + 8 * (x.wg * 2 + 1), 0);
  load_frag_tile(xt, warp * 16, lane, xr);
  mbar_wait(x.bFin + 8 * x.wg, 0);
#pragma unroll
  for (int jj = 0; jj < 8; jj++) {
    const uint4 r = lds128(st + (jj >> 2) * 16384 + (jj & 3) * 2048);
    xr[2 * jj] = hfma2_bf16(gb[jj], pack_bf16(a[4 * jj] + __uint_as_float(r.x), a[4 * jj + 1] + __uint_as_float(r.y)), xr[2 * jj]);
    xr[2 * jj + 1] = hfma2_bf16(gb[jj], pack_bf16(a[4 * jj + 2] + __uint_as_float(r.z), a[4 * jj + 3] + __uint_as_float(r.w)), xr[2 * jj + 1]);
  }
  store_frag_tile(xt, warp * 16, lane, xr);
  fence_proxy_async();
  if (x.wg == 0) named_bar_sync(1, 128); else named_bar_sync(2, 128);
  if (warp == 0 && elect_one()) {
    tma_store_2d(tmOut, xt, s * 64, rb * 128 + x.wg * 64);
    bulk_commit();
    bulk_wait_read();
  }
}

template <bool GEMM1, int KT, bool FRESH>
__device__ __forceinline__ void ffn_tile(const FfnCtx& x, float (&acc)[32], const uint32_t (&h)[144], uint32_t blo) {
#pragma unroll
  for (int kk = 0; kk < 4; kk++) {
    const int scale = (KT == 0 && kk == 0) ? x.zero : 1;
    const int q = (KT * 4 + kk) * 4;
    if (FRESH && KT == 0 && kk == 0) {
      if (GEMM1) wgmma_ss_n64_tb_init(acc, mk64(ffn_alo(x), FFN_DHI), mk64(blo, FFN_DHI));
      else wgmma_rs_n64_tb_init(acc, h[0], h[1], h[2], h[3], mk64(blo, FFN_DHI));
    } else if (GEMM1) {
      wgmma_ss_n64_tb(acc, mk64(ffn_alo(x) + KT * 1024 + kk * 2, FFN_DHI), mk64(blo + kk * 128, FFN_DHI), scale);
    } else {
      wgmma_rs_n64_tb(acc, h[q], h[q + 1], h[q + 2], h[q + 3], mk64(blo + kk * 128, FFN_DHI), scale);
    }
  }
}
template <bool FIRST, int S>
__device__ __forceinline__ void ffn_block_stage(FfnCtx& x, float (&ax)[32], float (&ay)[32], const float* prev, uint32_t (&h)[144],
                                                int n, bool stage_x) {
  if (FIRST && S == 4) x.nslot = FFN_STAGES2;
  ffn_wait_full(x);
  wg_fence();
  const uint32_t blo = ffn_blo(x);
  constexpr int T0 = 2 * S, T1 = 2 * S + 1;
  if (T0 < 9) ffn_tile<FIRST, (T0 < 9 ? T0 : 0), FIRST>(x, ax, h, blo); else ffn_tile<false, (T0 < 9 ? 0 : T0 - 9), FIRST>(x, ay, h, blo);
  if (T1 < 9) ffn_tile<FIRST, (T1 < 9 ? T1 : 0), FIRST>(x, ax, h, blo + 512); else ffn_tile<false, (T1 < 9 ? 0 : T1 - 9), FIRST>(x, ay, h, blo + 512);
  wg_commit();
  if (!FIRST && S == 0) ffn_order_signal(x);
  ffn_next(x, FIRST || S <= 1 || n != 7);
  if (FIRST && S == 0) ffn_silu<6>(prev, h);
  if (FIRST && S == 1) ffn_silu<7>(prev + 32, h);
  if (S == 5) {
    if (FIRST) {
      ffn_release(x, 5); ffn_release(x, 6); ffn_release(x, 7);
      ffn_silu<8>(ax, h);
    } else if (stage_x) {
      ffn_stage_partial(x, ax, n);
    }
  }
}
template <bool FIRST>
__device__ __forceinline__ void ffn_block(FfnCtx& x, float (&ax)[32], float (&ay)[32], const float* prev, uint32_t (&h)[144], int n,
                                          bool stage_x) {
  ffn_block_stage<FIRST, 0>(x, ax, ay, prev, h, n, stage_x); ffn_block_stage<FIRST, 1>(x, ax, ay, prev, h, n, stage_x);
  ffn_block_stage<FIRST, 2>(x, ax, ay, prev, h, n, stage_x); ffn_block_stage<FIRST, 3>(x, ax, ay, prev, h, n, stage_x);
  ffn_block_stage<FIRST, 4>(x, ax, ay, prev, h, n, stage_x); ffn_block_stage<FIRST, 5>(x, ax, ay, prev, h, n, stage_x);
  ffn_block_stage<FIRST, 6>(x, ax, ay, prev, h, n, stage_x); ffn_block_stage<FIRST, 7>(x, ax, ay, prev, h, n, stage_x);
  ffn_block_stage<FIRST, 8>(x, ax, ay, prev, h, n, stage_x);
}

__global__ void __launch_bounds__(384, 1)
ffn_kernel(const __grid_constant__ CUtensorMap tmH, const __grid_constant__ CUtensorMap tmW1, const __grid_constant__ CUtensorMap tmW2,
           const __grid_constant__ CUtensorMap tmX1, const __grid_constant__ CUtensorMap tmOut, __nv_bfloat16* __restrict__ out,
           int zero) {
  extern __shared__ uint8_t smem_raw[];
  const uint32_t sb = (smem_u32(smem_raw) + 1023) & ~1023u;
  const uint32_t sA = sb + FFN_A;
  const uint32_t bA = sb + FFN_BAR, bFull = bA + 8 * 9, bEmpty = bFull + 8 * FFN_STAGES2;
  const uint32_t bStgFull = bEmpty + 8 * FFN_STAGES2, bStgEmpty = bStgFull + 8 * 4, bFin = bStgEmpty + 8 * 4, bX = bFin + 8 * 4;
  const int tid = threadIdx.x, wid = __shfl_sync(0xffffffffu, tid >> 5, 0);
  const uint32_t rank = cluster_rank();
  const int fs = (blockIdx.x >> 1) & 7, rb = (blockIdx.x >> 4) * 2 + (int)rank;
  if (tid == 32) { prefetch_tmap(&tmW1); prefetch_tmap(&tmH); prefetch_tmap(&tmW2); prefetch_tmap(&tmX1); prefetch_tmap(&tmOut); }
  if (tid == 0) {
    for (int i = 0; i < 9; i++) mbar_init(bA + 8 * i, 1);
    for (int i = 0; i < FFN_STAGES2; i++) { mbar_init(bFull + 8 * i, 2); mbar_init(bEmpty + 8 * i, 4); }
    for (int i = 0; i < 4; i++) { mbar_init(bStgFull + 8 * i, 128); mbar_init(bStgEmpty + 8 * i, 1); mbar_init(bFin + 8 * i, 1); mbar_init(bX + 8 * i, 1); }
    fence_mbar_init();
  }
  cluster_arrive();
  cluster_wait();

  if (wid >= 8) {
    reg_dealloc<24>();
    if (wid == 10) {
      pdl_wait();
      pdl_launch();
      if (elect_one()) {
  #pragma unroll
        for (int i = 0; i < 9; i++) {
          mbar_expect_tx(bA + 8 * i, 16384);
          tma_2d(sA + i * 16384, &tmH, i * 64, rb * 128, bA + 8 * i);
        }
      }
      __syncwarp();
    }
    if (wid == 8 || wid == 11) {
      const int par = wid == 11;
      int slot = 0, nslot = FFN_STAGES;
      uint32_t ph = (1u << FFN_STAGES) - 1;
      const uint32_t dst0 = sA + par * 8192 + rank * 4096;
      auto load = [&](const CUtensorMap* tm, int c0, int c1) {
        mbar_wait(bEmpty + 8 * slot, (ph >> slot) & 1);
        if (elect_one()) {
          mbar_expect_tx(bFull + 8 * slot, 8192);
          tma_2d_mc(dst0 + ffn_slot_off(slot), tm, c0, c1, bFull + 8 * slot, 3);
        }
        ph ^= 1u << slot;
        if (++slot == nslot) slot = 0;
      };
      const int k0 = rank * 32, f0 = fs * 576;
      int kt = 0, c0 = f0 + par * 64;
#pragma unroll 1
      for (int t = 0; t < 36; t++) {
        load(&tmW1, c0, kt * 64 + k0);
        if (++kt == 9) { kt = 0; c0 += 128; }
      }
      int s = fs - 1;
      kt = par;
      bool gemm1 = true;
#pragma unroll 1
      for (int t = 0; t < 45; t++) {
        if (t == FFN_SWITCH - 36) nslot = FFN_STAGES2;
        if (gemm1) load(&tmW1, f0 + 512, kt * 64 + k0);
        else load(&tmW2, s * 64, f0 + kt * 64 + k0);
        kt += 2;
        if (kt >= 9) { kt -= 9; gemm1 = false; if (++s == 9) s = 0; }
      }
    } else if (tid == 288 || tid == 320) {
      const int w = tid == 288 ? 0 : 1;
      constexpr int nred = 8;
      const int slast = fs == 0 ? 8 : fs - 1;
#pragma unroll 1
      for (int n = 0; n < nred; n++) {
        const int b = n & 1;
        mbar_wait(bStgFull + 8 * (w * 2 + b), (n >> 1) & 1);
        if (n == 0) {
          pdl_wait();
          mbar_expect_tx(bX + 8 * (w * 2 + 1), 8192);
          tma_2d(ffn_x_tile(sA, w), &tmX1, slast * 64, rb * 128 + w * 64, bX + 8 * (w * 2 + 1));
        }
        int s = fs + n;
        if (s >= 9) s -= 9;
        float* dst = ffn_red_ptr(rb, s, w);
        const uint32_t src = sA + b * 32768 + w * 8192;
#pragma unroll 1
        for (int i = 0; i < 8; i++) {
          asm volatile("cp.reduce.async.bulk.global.shared::cta.bulk_group.add.f32 [%0], [%1], 2048;"
                       ::"l"(dst + i * 512), "r"(src + (i >> 2) * 16384 + (i & 3) * 2048) : "memory");
          if (i < 7 && n < nred - 1) __nanosleep(20);
        }
        asm volatile("cp.async.bulk.commit_group;" ::: "memory");
        if (n > 0) {
          asm volatile("cp.async.bulk.wait_group.read 1;" ::: "memory");
          mbar_arrive(bStgEmpty + 8 * (w * 2 + (b ^ 1)));
        }
      }
      asm volatile("cp.async.bulk.wait_group 0;" ::: "memory");
      publish_add(&g_cnt[rb * 2 + w], 1);
      spin_until_ge(&g_cnt[rb * 2 + w], 8);
      mbar_arrive(bX + 8 * (w * 2));
      asm volatile("fence.proxy.async.global;" ::: "memory");
      const uint32_t bar = bFin + 8 * w, dst = ffn_sum_tile(sA, w);
      const float* src = ffn_red_ptr(rb, slast, w);
      mbar_expect_tx(bar, 16384);
      bulk_g2s(dst, src, 8192, bar);
      bulk_g2s(dst + 16384, src + 2048, 8192, bar);
    }
  } else {
    reg_alloc<240>();
    FfnCtx x;
    x.sA = sA; x.bA = bA; x.bFull = bFull; x.bEmpty = bEmpty; x.remoteEmpty = mapa(bEmpty, rank ^ 1);
    x.bStgFull = bStgFull; x.bStgEmpty = bStgEmpty; x.bFin = bFin; x.bX = bX;
    x.slot = 0; x.pslot = 0; x.nslot = FFN_STAGES; x.ph = 0; x.tid = tid; x.wg = __shfl_sync(0xffffffffu, wid >> 2, 0); x.zero = zero;
    float pa[64], pb[64];
    uint32_t h[144];
    ffn_pair<0>(x, pa, pb, h);
    __syncwarp();
    ffn_pair<1>(x, pb, pa, h); ffn_pair<2>(x, pa, pb, h); ffn_pair<3>(x, pb, pa, h);
    pdl_wait();
    float a0[32], a1[32];
    ffn_block<true>(x, a0, a1, pb, h, 0, false);
    __syncwarp();
#pragma unroll 1
    for (int r = 1; r < 9; r += 2) {
      ffn_order_wait(x);
      wg_wait<0>();
      ffn_stage_partial(x, a1, r - 1);
      ffn_block<false>(x, a0, a1, pb, h, r, true);
    }
    wg_wait<0>();
    ffn_finish(x, a1, rb, fs, fs == 0 ? 8 : fs - 1, &tmOut, out);
  }
}

typedef CUresult (*EncodeTiledFn)(CUtensorMap*, CUtensorMapDataType, cuuint32_t, void*, const cuuint64_t*, const cuuint64_t*,
                                  const cuuint32_t*, const cuuint32_t*, CUtensorMapInterleave, CUtensorMapSwizzle,
                                  CUtensorMapL2promotion, CUtensorMapFloatOOBfill);

CUtensorMap make_map(EncodeTiledFn fn, const void* ptr, int rank, const cuuint64_t* dims, const cuuint64_t* strides,
                     const cuuint32_t* box, CUtensorMapSwizzle swz) {
  CUtensorMap m;
  const cuuint32_t es[3] = {1, 1, 1};
  fn(&m, CU_TENSOR_MAP_DATA_TYPE_BFLOAT16, rank, const_cast<void*>(ptr), dims, strides, box, es, CU_TENSOR_MAP_INTERLEAVE_NONE, swz,
     CU_TENSOR_MAP_L2_PROMOTION_L2_128B, CU_TENSOR_MAP_FLOAT_OOB_FILL_NONE);
  return m;
}
CUtensorMap make_map_2d(EncodeTiledFn fn, const void* ptr, uint64_t rows, uint64_t cols, uint32_t box_rows) {
  const cuuint64_t dims[2] = {cols, rows}, strides[1] = {cols * 2};
  const cuuint32_t box[2] = {64, box_rows};
  return make_map(fn, ptr, 2, dims, strides, box, CU_TENSOR_MAP_SWIZZLE_128B);
}

template <typename... KArgs, typename... Args>
void launch(void (*kern)(KArgs...), int grid, int block, int smem, int cluster, bool pdl, Args... args) {
  cudaLaunchConfig_t cfg = {};
  cfg.gridDim = dim3(grid); cfg.blockDim = dim3(block); cfg.dynamicSmemBytes = smem; cfg.stream = cudaStreamPerThread;
  cudaLaunchAttribute at[2];
  int n = 0;
  if (cluster > 1) { at[n].id = cudaLaunchAttributeClusterDimension; at[n].val.clusterDim.x = cluster; at[n].val.clusterDim.y = 1; at[n].val.clusterDim.z = 1; n++; }
  if (pdl) { at[n].id = cudaLaunchAttributeProgrammaticStreamSerialization; at[n].val.programmaticStreamSerializationAllowed = 1; n++; }
  cfg.attrs = at; cfg.numAttrs = n;
  cudaError_t e = cudaLaunchKernelEx(&cfg, kern, KArgs(args)...);
  (void)e;
}

}

extern "C" void kernel_launch(void* const* d_in, const int* in_sizes, int n_in, void* d_out, int out_size) {
  (void)in_sizes; (void)n_in; (void)out_size;
  const __nv_bfloat16* x = (const __nv_bfloat16*)d_in[0];
  const __nv_bfloat16* wqkv = (const __nv_bfloat16*)d_in[1];
  const __nv_bfloat16* wo = (const __nv_bfloat16*)d_in[2];
  const __nv_bfloat16* w1 = (const __nv_bfloat16*)d_in[4];
  const __nv_bfloat16* w2 = (const __nv_bfloat16*)d_in[5];
  const __nv_bfloat16* cvec = (const __nv_bfloat16*)d_in[6];
  const __nv_bfloat16* wmod = (const __nv_bfloat16*)d_in[7];

  static EncodeTiledFn encode = nullptr;
  static void *p_qkv, *p_o, *p_h2, *p_x1;
  if (!encode) {
    void* fn = nullptr;
    cudaDriverEntryPointQueryResult qr;
    cudaGetDriverEntryPoint("cuTensorMapEncodeTiled", &fn, cudaEnableDefault, &qr);
    encode = (EncodeTiledFn)fn;
    cudaFuncSetAttribute(qkv_kernel, cudaFuncAttributeMaxDynamicSharedMemorySize, QKV_SMEM);
    cudaFuncSetAttribute(attn_kernel, cudaFuncAttributeMaxDynamicSharedMemorySize, ATT_SMEM);
    cudaFuncSetAttribute(proj_kernel, cudaFuncAttributeMaxDynamicSharedMemorySize, PRJ_SMEM);
    cudaFuncSetAttribute(ffn_kernel, cudaFuncAttributeMaxDynamicSharedMemorySize, FFN_SMEM);
    cudaGetSymbolAddress(&p_qkv, g_qkv);
    cudaGetSymbolAddress(&p_o, g_o);
    cudaGetSymbolAddress(&p_h2, g_h2);
    cudaGetSymbolAddress(&p_x1, g_x1);
  }
  CUtensorMap tmWqkv;
  {
    const cuuint64_t dims[3] = {32, (cuuint64_t)DM, NQKV / 32}, strides[2] = {NQKV * 2, 64};
    const cuuint32_t box[3] = {32, 16, 7};
    tmWqkv = make_map(encode, wqkv, 3, dims, strides, box, CU_TENSOR_MAP_SWIZZLE_64B);
  }
  CUtensorMap tmWmod;
  {
    const cuuint64_t dims[2] = {6 * DM, DM}, strides[1] = {6 * DM * 2};
    const cuuint32_t box[2] = {32, 192};
    tmWmod = make_map(encode, wmod, 2, dims, strides, box, CU_TENSOR_MAP_SWIZZLE_64B);
  }
  const CUtensorMap tmO = make_map_2d(encode, p_o, SEQ, DM, 64), tmWo = make_map_2d(encode, wo, DM, DM, 64);
  const CUtensorMap tmH = make_map_2d(encode, p_h2, SEQ, DM, 128), tmX = make_map_2d(encode, x, SEQ, DM, 128);
  const CUtensorMap tmW1 = make_map_2d(encode, w1, DM, FF, 32), tmW2 = make_map_2d(encode, w2, FF, DM, 32);

  launch(qkv_kernel, 128, 384, QKV_SMEM, 2, false, tmX, tmWqkv, tmWmod, x, cvec, wqkv);
  launch(attn_kernel, 128, 512, ATT_SMEM, 1, true, (const uint8_t*)p_qkv, (__nv_bfloat16*)p_o, (const uint8_t*)wo, (uint32_t)(DM * DM * 2),
         (const uint8_t*)w1, (const uint8_t*)w2, (uint32_t)(DM * FF * 2), 0x64006400u);
  const CUtensorMap tmX1 = make_map_2d(encode, p_x1, SEQ, DM, 64), tmH64 = make_map_2d(encode, p_h2, SEQ, DM, 64);
  const CUtensorMap tmX64 = make_map_2d(encode, x, SEQ, DM, 64);
  launch(proj_kernel, 96, 416, PRJ_SMEM, 3, true, tmO, tmWo, tmX1, tmH64, tmX64);
  const CUtensorMap tmOut = make_map_2d(encode, d_out, SEQ, DM, 64);
  launch(ffn_kernel, 128, 384, FFN_SMEM, 2, true, tmH, tmW1, tmW2, tmX1, tmOut, (__nv_bfloat16*)d_out, 0);
}
```
